```python
import torch

def _softmax(x, axis=-1):
    return torch.softmax(x, dim=axis)

def _gelu(x):
    return torch.nn.functional.gelu(x, approximate='tanh')

def _silu(x):
    return torch.nn.functional.silu(x)

def _sigmoid(x):
    return torch.sigmoid(x)

def _layernorm(x, axis=-1, eps=1e-05):
    m = x.mean(dim=axis, keepdim=True)
    v = x.var(dim=axis, keepdim=True, unbiased=False)
    return (x - m) / torch.sqrt(v + eps)

def _scatter_add(tgt, idx, src, axis=0):
    return tgt.clone().index_add_(axis, idx, src)

def _segment_sum(src, seg, n):
    out = torch.zeros((n,) + src.shape[1:], dtype=src.dtype)
    return out.index_add_(0, seg, src)

def _pad(x, pw):
    flat = tuple((v for pair in reversed(pw) for v in pair))
    return torch.nn.functional.pad(x, flat)
kernel_name = 'adaLN_cond__sliding_local_dilated__glu_gated_glu__prompt'

def setup_inputs():

    _w = lambda a: (lambda t: t.to(torch.bfloat16) if t.is_floating_point() else t)(torch.as_tensor(a))

    def _A_setup():
        B, S, D = (1, 2048, 1024)
        return {'x': _w((lambda *s: torch.randn(*s, dtype=torch.bfloat16) * 0.05)(B, S, D)), 'wqkv': _w((lambda *s: torch.randn(*s, dtype=torch.bfloat16) * 0.05)(D, 3 * D)), 'wo': _w((lambda *s: torch.randn(*s, dtype=torch.bfloat16) * 0.05)(D, D))}
    _A_in = _A_setup()

    def _B_setup():
        B, S, D, F = (1, 2048, 1024, 3584)
        return {'x': _w((lambda *s: torch.randn(*s, dtype=torch.bfloat16) * 0.05)(B, S, D)), 'w_gate': _w((lambda *s: torch.randn(*s, dtype=torch.bfloat16) * 0.05)(D, F)), 'w_up': _w((lambda *s: torch.randn(*s, dtype=torch.bfloat16) * 0.05)(D, F)), 'w_down': _w((lambda *s: torch.randn(*s, dtype=torch.bfloat16) * 0.05)(F, D))}
    _B_in = _B_setup()
    return {'A_x': _A_in['x'], 'A_wqkv': _A_in['wqkv'], 'A_wo': _A_in['wo'], 'B_x': _B_in['x'], 'B_w_gate': _B_in['w_gate'], 'B_w_up': _B_in['w_up'], 'B_w_down': _B_in['w_down'], 'c': _w((lambda *s: torch.randn(*s, dtype=torch.bfloat16) * 0.1)(1, 1024) * 8.0), 'w_mod': _w((lambda *s: torch.randn(*s, dtype=torch.bfloat16) * 0.1)(1024, 6 * 1024) * 1024 ** (-0.5) * 8.0)}

def reference(A_x, A_wqkv, A_wo, B_x, B_w_gate, B_w_up, B_w_down, c, w_mod):

    def _A_ref(x, wqkv, wo):
        B, S, D = x.shape
        H = 32
        Dh = D // H
        W, dil = (8, 2)
        qkv = (lambda x, *d: x.permute(*d))((x @ wqkv).reshape(B, S, 3, H, Dh), 2, 0, 3, 1, 4)
        q, k, v = (qkv[0], qkv[1], qkv[2])
        scale = Dh ** (-0.5)
        pos = torch.arange(S)
        off = torch.arange(W) * dil
        idx = pos[:, None] - off[None, :]
        mask = idx >= 0
        idx_c = torch.where(mask, idx, 0).reshape(-1)
        kg = k[:, :, idx_c, :].reshape(B, H, S, W, Dh)
        vg = v[:, :, idx_c, :].reshape(B, H, S, W, Dh)
        logits = torch.einsum('bhsd,bhswd->bhsw', q, kg) * scale
        logits = torch.where(mask[None, None, :, :], logits, -1000000000.0)
        attn = _softmax(logits, axis=-1)
        o = torch.einsum('bhsw,bhswd->bhsd', attn, vg)
        return (lambda x, *d: x.permute(*d))(o, 0, 2, 1, 3).reshape(B, S, D) @ wo

    def _B_ref(x, w_gate, w_up, w_down):
        g = torch.einsum('bsd,df->bsf', x, w_gate)
        u = torch.einsum('bsd,df->bsf', x, w_up)
        h = _sigmoid(g) * u
        return torch.einsum('bsf,fd->bsd', h, w_down)
    x = A_x
    mod = (_silu(c) @ w_mod).reshape(c.shape[0], 6, 1, -1)
    sa, ca, ga, sb, cb, gb = (mod[:, 0].clone(), mod[:, 1].clone(), mod[:, 2].clone(), mod[:, 3].clone(), mod[:, 4].clone(), mod[:, 5].clone())
    h = _layernorm(x, axis=-1) * (1 + ca) + sa
    x = x + ga * _A_ref(h, A_wqkv, A_wo)
    h = _layernorm(x, axis=-1) * (1 + cb) + sb
    x = x + gb * _B_ref(h, B_w_gate, B_w_up, B_w_down)
    return x
```

```cpp
#include <cuda_runtime.h>
#include <cuda_bf16.h>
#include <cuda.h>
#include <stdint.h>
#include <stddef.h>

#define LAG 3
#define LAGS 2
#define LAGW 3
#define LAGD 3
#define LAGQ 3
#define EARLY 1
#define NQ 6
#define NS 5
#define TRIGO 255
#define RC 224
#define REST1 0
#define RESTO 0
#define RESTH 1000
#define HBM 0
#define NB0 2
#define EVB EV_PAR
#define EVS EV_WIN1
#define WARM 3
#define GW 4
#define GD 2
#define QA 3
#define UNSAFE 0
#define WFENCE 0

namespace {

constexpr int S_ = 2048, D_ = 1024, F_ = 3584;
constexpr int NCTA = 132;
constexpr int NSLOT = 6;
constexpr uint32_t SLOT = 32768;
constexpr uint32_t OFF_STG = NSLOT * SLOT;
constexpr uint32_t OFF_BAR = OFF_STG + 32768;
constexpr uint32_t OFF_PAR = OFF_BAR + 384;
constexpr uint32_t OFF_TAB = OFF_PAR + 512;
constexpr uint32_t OFF_JUNK = 0u - 1024;
constexpr uint32_t SMEM_BYTES = 1024 + OFF_TAB + 1024;
constexpr int ST_Q = 33, ST_WO = ST_Q + NQ + NS, ST_GU = ST_WO + 16, ST_G1 = ST_GU + 33;
static_assert(ST_GU % NSLOT == 0, "");
constexpr uint32_t OFF_OWN = 5 * SLOT;
constexpr uint32_t sweep_order() {
    uint32_t v = 0, n = 0;
    for (uint32_t want = 0; want < NSLOT; ++want)
        for (int i = 0; i < NS; ++i) { const uint32_t t = ST_WO - NS + i, s = t % NSLOT; if (s == want) v |= (s | (t / NSLOT & 1) << 3) << (4 * n++); }
    return v;
}
constexpr uint32_t SWEEP = sweep_order();

constexpr int FL_H1 = 0, FL_O = 16, FL_H2 = 32, FL_H = 48, FL_DONE = 16 * 64, FL_LN2 = 16 * 64 + 1;

enum { L_WQKV, L_WKV, L_WQ, L_WO, L_WG, L_WU, L_WD, L_WMOD, L_H1, L_H1Q, L_X, L_O, L_H2, L_HB, L_COUNT };
struct Maps {
    CUtensorMap wm, h1s, os, h1r, orr, hbr, out, ld[L_COUNT];
};

struct Mail {
    uint32_t flags[16 * 64 + 32];
    uint2 mod[6 * D_ / 2];
    uint4 mod1[8 * 2048];
    uint4 st1[8 * S_ / 2];
    uint32_t par2[D_];
    uint4 halo[128 * 512];
};
struct Ptrs { const __nv_bfloat16* c; Mail* mail; __nv_bfloat16* hb; };

__device__ __align__(128) Mail g_mail;
__device__ __align__(128) __nv_bfloat16 g_h1[S_ * D_];
__device__ __align__(128) __nv_bfloat16 g_o[S_ * D_];
__device__ __align__(128) __nv_bfloat16 g_hb[S_ * F_];
#define TS(i) do {} while (0)
#define TW(i) do {} while (0)
#define TX(i) do {} while (0)
#define TR(w, n) do {} while (0)

__device__ __forceinline__ uint32_t smem_u32(const void* p) { return (uint32_t)__cvta_generic_to_shared(p); }
__device__ __forceinline__ void mbar_init(uint32_t bar, uint32_t cnt) { asm volatile("mbarrier.init.shared::cta.b64 [%0], %1;" :: "r"(bar), "r"(cnt) : "memory"); }
__device__ __forceinline__ void mbar_expect_tx(uint32_t bar, uint32_t bytes) { asm volatile("mbarrier.arrive.expect_tx.shared::cta.b64 _, [%0], %1;" :: "r"(bar), "r"(bytes) : "memory"); }
__device__ __forceinline__ void mbar_arrive(uint32_t bar) { asm volatile("mbarrier.arrive.shared::cta.b64 _, [%0];" :: "r"(bar) : "memory"); }
__device__ __forceinline__ void mbar_arrive_if0(uint32_t bar, uint32_t z) {
    asm volatile("{\n.reg .pred p;\nsetp.eq.u32 p, %1, 0;\n@p mbarrier.arrive.shared::cta.b64 _, [%0];\n}" :: "r"(bar), "r"(z) : "memory");
}
__device__ __forceinline__ void mbar_wait(uint32_t bar, uint32_t parity) {
    asm volatile("{\n.reg .pred p;\nW_LOOP:\nmbarrier.try_wait.parity.shared::cta.b64 p, [%0], %1;\n@!p bra W_LOOP;\n}" :: "r"(bar), "r"(parity) : "memory");
}
__device__ __forceinline__ void mbar_wait_b(uint32_t bar, uint32_t parity) {
    asm volatile("{\n.reg .pred p;\n.reg .u32 n;\nmov.u32 n, 0;\n"
        "W_LOOP:\nmbarrier.try_wait.parity.shared::cta.b64 p, [%0], %1;\n@p bra W_DONE;\n"
        "add.u32 n, n, 1;\nsetp.lt.u32 p, n, 0x400000;\n@p bra W_LOOP;\ntrap;\nW_DONE:\n}" :: "r"(bar), "r"(parity) : "memory");
}
__device__ __forceinline__ void tma_load(uint32_t dst, const CUtensorMap* m, int c0, int c1, uint32_t bar) {
    asm volatile("cp.async.bulk.tensor.2d.shared::cluster.global.mbarrier::complete_tx::bytes [%0], [%1, {%3, %4}], [%2];"
        :: "r"(dst), "l"(m), "r"(bar), "r"(c0), "r"(c1) : "memory");
}
__device__ __forceinline__ void tma_load4(uint32_t dst, const CUtensorMap* m, int c0, int c1, int c2, uint32_t bar) {
    asm volatile("cp.async.bulk.tensor.4d.shared::cluster.global.mbarrier::complete_tx::bytes [%0], [%1, {%3, %4, %5, %6}], [%2];"
        :: "r"(dst), "l"(m), "r"(bar), "r"(c0), "r"(c1), "r"(c2), "r"(0) : "memory");
}
__device__ __forceinline__ void tma_load5_mc(uint32_t dst, const CUtensorMap* m, int c0, int c1, int c2, int c3, int c4, uint32_t bar) {
    asm volatile("cp.async.bulk.tensor.5d.shared::cluster.global.mbarrier::complete_tx::bytes.multicast::cluster.L2::cache_hint [%0], [%1, {%3, %4, %5, %6, %7}], [%2], %8, %9;"
        :: "r"(dst), "l"(m), "r"(bar), "r"(c0), "r"(c1), "r"(c2), "r"(c3), "r"(c4), "h"((uint16_t)3), "l"(0x12F0000000000000ull) : "memory");
}
__device__ __forceinline__ void tma_store(const CUtensorMap* m, int c0, int c1, uint32_t src) {
    asm volatile("cp.async.bulk.tensor.2d.global.shared::cta.bulk_group [%0, {%2, %3}], [%1];" :: "l"(m), "r"(src), "r"(c0), "r"(c1) : "memory");
}
__device__ __forceinline__ void bulk_commit() { asm volatile("cp.async.bulk.commit_group;" ::: "memory"); }
__device__ __forceinline__ void bulk_wait_read() { asm volatile("cp.async.bulk.wait_group.read 0;" ::: "memory"); }
__device__ __forceinline__ void bulk_wait_all() { asm volatile("cp.async.bulk.wait_group 0;" ::: "memory"); }
__device__ __forceinline__ void fence_async_smem() { asm volatile("fence.proxy.async.shared::cta;" ::: "memory"); }
__device__ __forceinline__ void fence_async_global() { asm volatile("fence.proxy.async.global;" ::: "memory"); }
__device__ __forceinline__ void prefetch_map(const CUtensorMap* m) { asm volatile("prefetch.tensormap [%0];" :: "l"(m) : "memory"); }
__device__ __forceinline__ void wg_fence() { asm volatile("wgmma.fence.sync.aligned;" ::: "memory"); }
__device__ __forceinline__ void wg_commit() { asm volatile("wgmma.commit_group.sync.aligned;" ::: "memory"); }
template <int N> __device__ __forceinline__ void wg_wait() { asm volatile("wgmma.wait_group.sync.aligned %0;" :: "n"(N) : "memory"); }
__device__ __forceinline__ void bar_sync(int id, int n) { asm volatile("bar.sync %0, %1;" :: "r"(id), "r"(n) : "memory"); }
__device__ __forceinline__ void flag_add(uint32_t* f) { asm volatile("red.relaxed.gpu.global.add.u32 [%0], 1;" :: "l"(f) : "memory"); }
__device__ __forceinline__ uint32_t d16(uint32_t addr) { return (addr & 0x3FFFF) >> 4; }
__device__ __forceinline__ uint64_t mk_desc(uint32_t a16, uint32_t off, uint32_t lbo, uint32_t sbo, uint32_t swz) {
    const uint32_t lo = a16 + (off >> 4) + ((lbo >> 4) << 16), hi = (sbo >> 4) | (swz << 30);
    return ((uint64_t)hi << 32) | lo;
}
__device__ __forceinline__ uint32_t pack2(float lo, float hi) {
    uint32_t r; asm("cvt.rn.bf16x2.f32 %0, %1, %2;" : "=r"(r) : "f"(hi), "f"(lo)); return r;
}
__device__ __forceinline__ uint32_t hfma2_bf16(uint32_t a, uint32_t b, uint32_t c) {
    uint32_t r; asm("fma.rn.bf16x2 %0, %1, %2, %3;" : "=r"(r) : "r"(a), "r"(b), "r"(c)); return r;
}
__device__ __forceinline__ float bf_lo(uint32_t v) { return __uint_as_float(v << 16); }
__device__ __forceinline__ float bf_hi(uint32_t v) { return __uint_as_float(v & 0xFFFF0000u); }
__device__ __forceinline__ float bf_round(float x) { return __bfloat162float(__float2bfloat16_rn(x)); }
__device__ __forceinline__ void stsm4(uint32_t addr, uint32_t r0, uint32_t r1, uint32_t r2, uint32_t r3) {
    asm volatile("stmatrix.sync.aligned.m8n8.x4.shared.b16 [%0], {%1, %2, %3, %4};" :: "r"(addr), "r"(r0), "r"(r1), "r"(r2), "r"(r3) : "memory");
}
__device__ __forceinline__ void stsm4t(uint32_t addr, uint32_t r0, uint32_t r1, uint32_t r2, uint32_t r3) {
    asm volatile("stmatrix.sync.aligned.m8n8.x4.trans.shared.b16 [%0], {%1, %2, %3, %4};" :: "r"(addr), "r"(r0), "r"(r1), "r"(r2), "r"(r3) : "memory");
}
__device__ __forceinline__ void ldsm4(uint32_t addr, uint32_t& r0, uint32_t& r1, uint32_t& r2, uint32_t& r3) {
    asm volatile("ldmatrix.sync.aligned.m8n8.x4.shared.b16 {%0, %1, %2, %3}, [%4];" : "=r"(r0), "=r"(r1), "=r"(r2), "=r"(r3) : "r"(addr) : "memory");
}
__device__ __forceinline__ uint32_t movm(uint32_t a) { uint32_t r; asm volatile("movmatrix.sync.aligned.m8n8.trans.b16 %0, %1;" : "=r"(r) : "r"(a)); return r; }
__device__ __forceinline__ void mma16816(float (&c)[4], uint32_t a0, uint32_t a1, uint32_t a2, uint32_t a3, uint32_t b0, uint32_t b1) {
    asm("mma.sync.aligned.m16n8k16.row.col.f32.bf16.bf16.f32 {%0, %1, %2, %3}, {%4, %5, %6, %7}, {%8, %9}, {%0, %1, %2, %3};"
        : "+f"(c[0]), "+f"(c[1]), "+f"(c[2]), "+f"(c[3]) : "r"(a0), "r"(a1), "r"(a2), "r"(a3), "r"(b0), "r"(b1));
}
__device__ __forceinline__ float ex2(float x) { float r; asm("ex2.approx.ftz.f32 %0, %1;" : "=f"(r) : "f"(x)); return r; }
__device__ __forceinline__ float rcp(float x) { float r; asm("rcp.approx.ftz.f32 %0, %1;" : "=f"(r) : "f"(x)); return r; }
__device__ __forceinline__ float rsq(float x) { float r; asm("rsqrt.approx.ftz.f32 %0, %1;" : "=f"(r) : "f"(x)); return r; }
__device__ __forceinline__ float silu_(float x) { return __fdividef(x, 1.f + __expf(-x)); }
__device__ __forceinline__ void st_pkt(void* p, uint32_t a, uint32_t b) {
    asm volatile("{\n.reg .b64 t;\nmov.b64 t, {%1, %2};\nst.relaxed.gpu.global.b64 [%0], t;\n}" :: "l"(p), "r"(a), "r"(b) : "memory");
}
__device__ __forceinline__ uint2 ld_pkt(const void* p) {
    uint2 v; asm volatile("{\n.reg .b64 t;\nld.relaxed.gpu.global.b64 t, [%2];\nmov.b64 {%0, %1}, t;\n}" : "=r"(v.x), "=r"(v.y) : "l"(p) : "memory"); return v;
}
__device__ __forceinline__ void st_pkt16(void* p, uint32_t a, uint32_t b, uint32_t c, uint32_t d) {
    asm volatile("{\n.reg .b64 t, u;\n.reg .b128 w;\nmov.b64 t, {%1, %2};\nmov.b64 u, {%3, %4};\nmov.b128 w, {t, u};\nst.relaxed.gpu.global.b128 [%0], w;\n}"
        :: "l"(p), "r"(a), "r"(b), "r"(c), "r"(d) : "memory");
}
__device__ __forceinline__ uint4 ld_pkt16(const void* p) {
    uint4 v; asm volatile("{\n.reg .b64 t, u;\n.reg .b128 w;\nld.relaxed.gpu.global.b128 w, [%4];\nmov.b128 {t, u}, w;\nmov.b64 {%0, %1}, t;\nmov.b64 {%2, %3}, u;\n}"
        : "=r"(v.x), "=r"(v.y), "=r"(v.z), "=r"(v.w) : "l"(p) : "memory"); return v;
}
#define SPIN_GUARD(n) do { if (++(n) > (1u << 22)) asm volatile("trap;"); } while (0)
__device__ __forceinline__ uint4 lds128(uint32_t a) { uint4 v; asm volatile("ld.shared.v4.u32 {%0, %1, %2, %3}, [%4];" : "=r"(v.x), "=r"(v.y), "=r"(v.z), "=r"(v.w) : "r"(a) : "memory"); return v; }
__device__ __forceinline__ void sts128(uint32_t a, uint32_t x, uint32_t y, uint32_t z, uint32_t w) { asm volatile("st.shared.v4.u32 [%0], {%1, %2, %3, %4};" :: "r"(a), "r"(x), "r"(y), "r"(z), "r"(w) : "memory"); }
__device__ __forceinline__ uint2 lds64(uint32_t a) { uint2 v; asm volatile("ld.shared.v2.u32 {%0, %1}, [%2];" : "=r"(v.x), "=r"(v.y) : "r"(a) : "memory"); return v; }
__device__ __forceinline__ void sts64(uint32_t a, uint32_t x, uint32_t y) { asm volatile("st.shared.v2.u32 [%0], {%1, %2};" :: "r"(a), "r"(x), "r"(y) : "memory"); }
__device__ __forceinline__ uint32_t lds32(uint32_t a) { uint32_t v; asm volatile("ld.shared.u32 %0, [%1];" : "=r"(v) : "r"(a) : "memory"); return v; }
__device__ __forceinline__ void sts32(uint32_t a, uint32_t v) { asm volatile("st.shared.u32 [%0], %1;" :: "r"(a), "r"(v) : "memory"); }
__device__ __forceinline__ bool elect_one() {
    uint32_t p; asm volatile("{\n.reg .pred q;\nelect.sync _|q, 0xffffffff;\nselp.u32 %0, 1, 0, q;\n}" : "=r"(p)); return p;
}
__device__ __forceinline__ void cluster_arrive() { asm volatile("barrier.cluster.arrive.relaxed.aligned;" ::: "memory"); }
__device__ __forceinline__ void cluster_wait() { asm volatile("barrier.cluster.wait.aligned;" ::: "memory"); }

__device__ __forceinline__ void wgmma_n128_z(float (&d)[64], uint64_t da, uint64_t db) {
    asm volatile("{\n.reg .pred p;\nsetp.ne.b32 p, 0, 0;\n"
        "wgmma.mma_async.sync.aligned.m64n128k16.f32.bf16.bf16 {"
        "%0, %1, %2, %3, %4, %5, %6, %7, %8, %9, %10, %11, %12, %13, %14, %15, "
        "%16, %17, %18, %19, %20, %21, %22, %23, %24, %25, %26, %27, %28, %29, %30, %31, "
        "%32, %33, %34, %35, %36, %37, %38, %39, %40, %41, %42, %43, %44, %45, %46, %47, "
        "%48, %49, %50, %51, %52, %53, %54, %55, %56, %57, %58, %59, %60, %61, %62, %63"
        "}, %64, %65, p, 1, 1, 0, 1;\n}\n"
        : "=f"(d[0]), "=f"(d[1]), "=f"(d[2]), "=f"(d[3]), "=f"(d[4]), "=f"(d[5]), "=f"(d[6]), "=f"(d[7]),
          "=f"(d[8]), "=f"(d[9]), "=f"(d[10]), "=f"(d[11]), "=f"(d[12]), "=f"(d[13]), "=f"(d[14]), "=f"(d[15]),
          "=f"(d[16]), "=f"(d[17]), "=f"(d[18]), "=f"(d[19]), "=f"(d[20]), "=f"(d[21]), "=f"(d[22]), "=f"(d[23]),
          "=f"(d[24]), "=f"(d[25]), "=f"(d[26]), "=f"(d[27]), "=f"(d[28]), "=f"(d[29]), "=f"(d[30]), "=f"(d[31]),
          "=f"(d[32]), "=f"(d[33]), "=f"(d[34]), "=f"(d[35]), "=f"(d[36]), "=f"(d[37]), "=f"(d[38]), "=f"(d[39]),
          "=f"(d[40]), "=f"(d[41]), "=f"(d[42]), "=f"(d[43]), "=f"(d[44]), "=f"(d[45]), "=f"(d[46]), "=f"(d[47]),
          "=f"(d[48]), "=f"(d[49]), "=f"(d[50]), "=f"(d[51]), "=f"(d[52]), "=f"(d[53]), "=f"(d[54]), "=f"(d[55]),
          "=f"(d[56]), "=f"(d[57]), "=f"(d[58]), "=f"(d[59]), "=f"(d[60]), "=f"(d[61]), "=f"(d[62]), "=f"(d[63])
        : "l"(da), "l"(db));
}
__device__ __forceinline__ void wgmma_n128(float (&d)[64], uint64_t da, uint64_t db) {
    asm volatile("{\n.reg .pred p;\nsetp.eq.b32 p, 0, 0;\n"
        "wgmma.mma_async.sync.aligned.m64n128k16.f32.bf16.bf16 {"
        "%0, %1, %2, %3, %4, %5, %6, %7, %8, %9, %10, %11, %12, %13, %14, %15, "
        "%16, %17, %18, %19, %20, %21, %22, %23, %24, %25, %26, %27, %28, %29, %30, %31, "
        "%32, %33, %34, %35, %36, %37, %38, %39, %40, %41, %42, %43, %44, %45, %46, %47, "
        "%48, %49, %50, %51, %52, %53, %54, %55, %56, %57, %58, %59, %60, %61, %62, %63"
        "}, %64, %65, p, 1, 1, 0, 1;\n}\n"
        : "+f"(d[0]), "+f"(d[1]), "+f"(d[2]), "+f"(d[3]), "+f"(d[4]), "+f"(d[5]), "+f"(d[6]), "+f"(d[7]),
          "+f"(d[8]), "+f"(d[9]), "+f"(d[10]), "+f"(d[11]), "+f"(d[12]), "+f"(d[13]), "+f"(d[14]), "+f"(d[15]),
          "+f"(d[16]), "+f"(d[17]), "+f"(d[18]), "+f"(d[19]), "+f"(d[20]), "+f"(d[21]), "+f"(d[22]), "+f"(d[23]),
          "+f"(d[24]), "+f"(d[25]), "+f"(d[26]), "+f"(d[27]), "+f"(d[28]), "+f"(d[29]), "+f"(d[30]), "+f"(d[31]),
          "+f"(d[32]), "+f"(d[33]), "+f"(d[34]), "+f"(d[35]), "+f"(d[36]), "+f"(d[37]), "+f"(d[38]), "+f"(d[39]),
          "+f"(d[40]), "+f"(d[41]), "+f"(d[42]), "+f"(d[43]), "+f"(d[44]), "+f"(d[45]), "+f"(d[46]), "+f"(d[47]),
          "+f"(d[48]), "+f"(d[49]), "+f"(d[50]), "+f"(d[51]), "+f"(d[52]), "+f"(d[53]), "+f"(d[54]), "+f"(d[55]),
          "+f"(d[56]), "+f"(d[57]), "+f"(d[58]), "+f"(d[59]), "+f"(d[60]), "+f"(d[61]), "+f"(d[62]), "+f"(d[63])
        : "l"(da), "l"(db));
}
__device__ __forceinline__ void wgmma_n256_z(float (&d)[128], uint64_t da, uint64_t db) {
    asm volatile("{\n.reg .pred p;\nsetp.ne.b32 p, 0, 0;\n"
        "wgmma.mma_async.sync.aligned.m64n256k16.f32.bf16.bf16 {"
        "%0, %1, %2, %3, %4, %5, %6, %7, %8, %9, %10, %11, %12, %13, %14, %15, "
        "%16, %17, %18, %19, %20, %21, %22, %23, %24, %25, %26, %27, %28, %29, %30, %31, "
        "%32, %33, %34, %35, %36, %37, %38, %39, %40, %41, %42, %43, %44, %45, %46, %47, "
        "%48, %49, %50, %51, %52, %53, %54, %55, %56, %57, %58, %59, %60, %61, %62, %63, "
        "%64, %65, %66, %67, %68, %69, %70, %71, %72, %73, %74, %75, %76, %77, %78, %79, "
        "%80, %81, %82, %83, %84, %85, %86, %87, %88, %89, %90, %91, %92, %93, %94, %95, "
        "%96, %97, %98, %99, %100, %101, %102, %103, %104, %105, %106, %107, %108, %109, %110, %111, "
        "%112, %113, %114, %115, %116, %117, %118, %119, %120, %121, %122, %123, %124, %125, %126, %127"
        "}, %128, %129, p, 1, 1, 0, 1;\n}\n"
        : "=f"(d[0]), "=f"(d[1]), "=f"(d[2]), "=f"(d[3]), "=f"(d[4]), "=f"(d[5]), "=f"(d[6]), "=f"(d[7]),
          "=f"(d[8]), "=f"(d[9]), "=f"(d[10]), "=f"(d[11]), "=f"(d[12]), "=f"(d[13]), "=f"(d[14]), "=f"(d[15]),
          "=f"(d[16]), "=f"(d[17]), "=f"(d[18]), "=f"(d[19]), "=f"(d[20]), "=f"(d[21]), "=f"(d[22]), "=f"(d[23]),
          "=f"(d[24]), "=f"(d[25]), "=f"(d[26]), "=f"(d[27]), "=f"(d[28]), "=f"(d[29]), "=f"(d[30]), "=f"(d[31]),
          "=f"(d[32]), "=f"(d[33]), "=f"(d[34]), "=f"(d[35]), "=f"(d[36]), "=f"(d[37]), "=f"(d[38]), "=f"(d[39]),
          "=f"(d[40]), "=f"(d[41]), "=f"(d[42]), "=f"(d[43]), "=f"(d[44]), "=f"(d[45]), "=f"(d[46]), "=f"(d[47]),
          "=f"(d[48]), "=f"(d[49]), "=f"(d[50]), "=f"(d[51]), "=f"(d[52]), "=f"(d[53]), "=f"(d[54]), "=f"(d[55]),
          "=f"(d[56]), "=f"(d[57]), "=f"(d[58]), "=f"(d[59]), "=f"(d[60]), "=f"(d[61]), "=f"(d[62]), "=f"(d[63]),
          "=f"(d[64]), "=f"(d[65]), "=f"(d[66]), "=f"(d[67]), "=f"(d[68]), "=f"(d[69]), "=f"(d[70]), "=f"(d[71]),
          "=f"(d[72]), "=f"(d[73]), "=f"(d[74]), "=f"(d[75]), "=f"(d[76]), "=f"(d[77]), "=f"(d[78]), "=f"(d[79]),
          "=f"(d[80]), "=f"(d[81]), "=f"(d[82]), "=f"(d[83]), "=f"(d[84]), "=f"(d[85]), "=f"(d[86]), "=f"(d[87]),
          "=f"(d[88]), "=f"(d[89]), "=f"(d[90]), "=f"(d[91]), "=f"(d[92]), "=f"(d[93]), "=f"(d[94]), "=f"(d[95]),
          "=f"(d[96]), "=f"(d[97]), "=f"(d[98]), "=f"(d[99]), "=f"(d[100]), "=f"(d[101]), "=f"(d[102]), "=f"(d[103]),
          "=f"(d[104]), "=f"(d[105]), "=f"(d[106]), "=f"(d[107]), "=f"(d[108]), "=f"(d[109]), "=f"(d[110]), "=f"(d[111]),
          "=f"(d[112]), "=f"(d[113]), "=f"(d[114]), "=f"(d[115]), "=f"(d[116]), "=f"(d[117]), "=f"(d[118]), "=f"(d[119]),
          "=f"(d[120]), "=f"(d[121]), "=f"(d[122]), "=f"(d[123]), "=f"(d[124]), "=f"(d[125]), "=f"(d[126]), "=f"(d[127])
        : "l"(da), "l"(db));
}
__device__ __forceinline__ void wgmma_n256(float (&d)[128], uint64_t da, uint64_t db) {
    asm volatile("{\n.reg .pred p;\nsetp.eq.b32 p, 0, 0;\n"
        "wgmma.mma_async.sync.aligned.m64n256k16.f32.bf16.bf16 {"
        "%0, %1, %2, %3, %4, %5, %6, %7, %8, %9, %10, %11, %12, %13, %14, %15, "
        "%16, %17, %18, %19, %20, %21, %22, %23, %24, %25, %26, %27, %28, %29, %30, %31, "
        "%32, %33, %34, %35, %36, %37, %38, %39, %40, %41, %42, %43, %44, %45, %46, %47, "
        "%48, %49, %50, %51, %52, %53, %54, %55, %56, %57, %58, %59, %60, %61, %62, %63, "
        "%64, %65, %66, %67, %68, %69, %70, %71, %72, %73, %74, %75, %76, %77, %78, %79, "
        "%80, %81, %82, %83, %84, %85, %86, %87, %88, %89, %90, %91, %92, %93, %94, %95, "
        "%96, %97, %98, %99, %100, %101, %102, %103, %104, %105, %106, %107, %108, %109, %110, %111, "
        "%112, %113, %114, %115, %116, %117, %118, %119, %120, %121, %122, %123, %124, %125, %126, %127"
        "}, %128, %129, p, 1, 1, 0, 1;\n}\n"
        : "+f"(d[0]), "+f"(d[1]), "+f"(d[2]), "+f"(d[3]), "+f"(d[4]), "+f"(d[5]), "+f"(d[6]), "+f"(d[7]),
          "+f"(d[8]), "+f"(d[9]), "+f"(d[10]), "+f"(d[11]), "+f"(d[12]), "+f"(d[13]), "+f"(d[14]), "+f"(d[15]),
          "+f"(d[16]), "+f"(d[17]), "+f"(d[18]), "+f"(d[19]), "+f"(d[20]), "+f"(d[21]), "+f"(d[22]), "+f"(d[23]),
          "+f"(d[24]), "+f"(d[25]), "+f"(d[26]), "+f"(d[27]), "+f"(d[28]), "+f"(d[29]), "+f"(d[30]), "+f"(d[31]),
          "+f"(d[32]), "+f"(d[33]), "+f"(d[34]), "+f"(d[35]), "+f"(d[36]), "+f"(d[37]), "+f"(d[38]), "+f"(d[39]),
          "+f"(d[40]), "+f"(d[41]), "+f"(d[42]), "+f"(d[43]), "+f"(d[44]), "+f"(d[45]), "+f"(d[46]), "+f"(d[47]),
          "+f"(d[48]), "+f"(d[49]), "+f"(d[50]), "+f"(d[51]), "+f"(d[52]), "+f"(d[53]), "+f"(d[54]), "+f"(d[55]),
          "+f"(d[56]), "+f"(d[57]), "+f"(d[58]), "+f"(d[59]), "+f"(d[60]), "+f"(d[61]), "+f"(d[62]), "+f"(d[63]),
          "+f"(d[64]), "+f"(d[65]), "+f"(d[66]), "+f"(d[67]), "+f"(d[68]), "+f"(d[69]), "+f"(d[70]), "+f"(d[71]),
          "+f"(d[72]), "+f"(d[73]), "+f"(d[74]), "+f"(d[75]), "+f"(d[76]), "+f"(d[77]), "+f"(d[78]), "+f"(d[79]),
          "+f"(d[80]), "+f"(d[81]), "+f"(d[82]), "+f"(d[83]), "+f"(d[84]), "+f"(d[85]), "+f"(d[86]), "+f"(d[87]),
          "+f"(d[88]), "+f"(d[89]), "+f"(d[90]), "+f"(d[91]), "+f"(d[92]), "+f"(d[93]), "+f"(d[94]), "+f"(d[95]),
          "+f"(d[96]), "+f"(d[97]), "+f"(d[98]), "+f"(d[99]), "+f"(d[100]), "+f"(d[101]), "+f"(d[102]), "+f"(d[103]),
          "+f"(d[104]), "+f"(d[105]), "+f"(d[106]), "+f"(d[107]), "+f"(d[108]), "+f"(d[109]), "+f"(d[110]), "+f"(d[111]),
          "+f"(d[112]), "+f"(d[113]), "+f"(d[114]), "+f"(d[115]), "+f"(d[116]), "+f"(d[117]), "+f"(d[118]), "+f"(d[119]),
          "+f"(d[120]), "+f"(d[121]), "+f"(d[122]), "+f"(d[123]), "+f"(d[124]), "+f"(d[125]), "+f"(d[126]), "+f"(d[127])
        : "l"(da), "l"(db));
}
template <int O, int L>
__device__ __forceinline__ void wgmma_n64(float (&d)[L], uint64_t da, uint64_t db) {
    asm volatile("{\n.reg .pred p;\nsetp.eq.b32 p, 0, 0;\n"
        "wgmma.mma_async.sync.aligned.m64n64k16.f32.bf16.bf16 {%0, %1, %2, %3, %4, %5, %6, %7, %8, %9, %10, %11, %12, %13, %14, %15, %16, %17, %18, %19, %20, %21, %22, %23, %24, %25, %26, %27, %28, %29, %30, %31}, %32, %33, p, 1, 1, 0, 1;\n}\n"
        : "+f"(d[O + 0]), "+f"(d[O + 1]), "+f"(d[O + 2]), "+f"(d[O + 3]), "+f"(d[O + 4]), "+f"(d[O + 5]), "+f"(d[O + 6]), "+f"(d[O + 7]),
          "+f"(d[O + 8]), "+f"(d[O + 9]), "+f"(d[O + 10]), "+f"(d[O + 11]), "+f"(d[O + 12]), "+f"(d[O + 13]), "+f"(d[O + 14]), "+f"(d[O + 15]),
          "+f"(d[O + 16]), "+f"(d[O + 17]), "+f"(d[O + 18]), "+f"(d[O + 19]), "+f"(d[O + 20]), "+f"(d[O + 21]), "+f"(d[O + 22]), "+f"(d[O + 23]),
          "+f"(d[O + 24]), "+f"(d[O + 25]), "+f"(d[O + 26]), "+f"(d[O + 27]), "+f"(d[O + 28]), "+f"(d[O + 29]), "+f"(d[O + 30]), "+f"(d[O + 31])
        : "l"(da), "l"(db));
}

struct Idx {
    uint32_t lane, warp, w4, q4, g8, prow, pan;
    __device__ __forceinline__ Idx() {
        uint32_t t; asm volatile("mov.u32 %0, %%tid.x;" : "=r"(t));
        lane = t & 31; warp = t >> 5; w4 = warp & 3; q4 = lane & 3; g8 = lane >> 2;
        prow = w4 * 16 + ((lane >> 3) & 1) * 8 + (lane & 7);
        pan = prow * 128 + (((lane >> 4) ^ (lane & 7)) << 4);
    }
};
#define IDX() const Idx ix; const uint32_t lane = ix.lane, warp = ix.warp, w4 = ix.w4, q4 = ix.q4, g8 = ix.g8, prow = ix.prow, pan_addr = ix.pan; \
    (void)lane; (void)warp; (void)w4; (void)q4; (void)g8; (void)prow; (void)pan_addr;

struct Ring {
    uint32_t slot, par;
    __device__ __forceinline__ void next() { if (++slot == NSLOT) { slot = 0; par ^= 1; } }
};
__device__ __forceinline__ uint32_t BAR_FULL(uint32_t sb, uint32_t s) { return sb + OFF_BAR + 8 * s; }
__device__ __forceinline__ uint32_t BAR_EMPTY(uint32_t sb, uint32_t s) { return sb + OFF_BAR + 48 + 8 * s; }
__device__ __forceinline__ uint32_t BAR_SFULL(uint32_t sb, uint32_t i) { return sb + OFF_BAR + 96 + 8 * i; }
__device__ __forceinline__ uint32_t BAR_ONE(uint32_t sb, uint32_t i) { return sb + OFF_BAR + 160 + 8 * i; }
enum { EV_X, EV_WIN, EV_WIN1, EV_GA, EV_GB, EV_LAG0, EV_LAG1, EV_LAG2, EV_LAG3, EV_LAG4, EV_LAG5, EV_HB, EV_H, EV_H1, EV_H2, EV_SENT, EV_SEC, EV_BACK, EV_BACK1, EV_GO, EV_PAR, EV_COUNT };

enum { K_ABS, K_OWN, K_PANEL };
enum { F_WRAP = 1, F_TWICE = 2, F_SKIP = 4 };
constexpr uint32_t pre_ev(uint32_t ev) { return 160 + 8 * ev; }
constexpr uint32_t pre_sfull(uint32_t par) { return 96 + par; }
constexpr uint4 seg(uint32_t n, uint32_t kind, uint32_t a, uint32_t step, uint32_t q, uint32_t jump, uint32_t flags, uint32_t map, uint32_t kb, uint32_t pre = 0,
                    uint32_t blkj = 0, uint32_t blk = 0, uint32_t split = 0, uint32_t fl = 0, uint32_t cnt = 0) {
    return uint4{n | (127 + q) / q << 8 | flags << 16 | map << 24, kind | a << 2 | step << 16 | jump / 64 << 24, kb | blkj << 8 | blk << 12 | split << 20, pre | fl << 16 | cnt << 24};
}
constexpr int NSEG = 15;
__device__ const uint4 g_sched[3][NSEG] = {
    {seg(NB0, K_ABS, 0, 0, 1, 0, F_SKIP, L_WQKV, 0),
     seg(4 - NB0, K_OWN, NB0, 32, 32, 0, F_TWICE, L_WQKV, 24, pre_ev(EVB), 2, 0, 1),
     seg(28 - 2 * NQ, K_PANEL, 0, 32, 2, 64, F_WRAP, L_WQKV, 24, 0, 2, 0, 1), seg(2 * NQ, K_PANEL, 28 - 2 * NQ, 32, 2, 64, 0, L_WKV, 16, 0, 2, 0, 1),
     seg(NQ, K_PANEL, 28 - 2 * NQ, 64, 1, 64, 0, L_WQ, 16, 0, 2, 0, 3), seg(NS, K_PANEL, 28 - 2 * NQ - 2 * NS, 64, 1, 64, 0, L_WQ, 16, 0, 2, 0, 3),
     seg(2, K_OWN, 0, 64, 32, 0, 0, L_WO, 16, 0, 2, 0, 3), seg(14, K_PANEL, 0, 64, 1, 64, 0, L_WO, 16, 0, 2, 0, 3),
     seg(4, K_OWN, 0, 32, 32, 0, F_TWICE, L_WG, 24, 0, 7, 0, 2), seg(28, K_PANEL, 0, 32, 2, 64, F_WRAP, L_WG, 24, 0, 7, 0, 2),
     seg(32, K_ABS, 0, 32, 32, 0, 0, L_WG, 16, 0, 7, 3, 2), seg(32, K_ABS, 0, 32, 32, 0, 0, L_WG, 16, 0, 7, 5, 2),
     seg(24, K_ABS, 0, 64, 3, 256, 0, L_WD, 16, 0, 2, 0, 3), seg(16, K_ABS, 6, 64, 2, 320, 0, L_WD, 16, 0, 2, 0, 3), seg(16, K_ABS, 10, 64, 2, 320, 0, L_WD, 16, 0, 2, 0, 3)},
    {seg(4, K_ABS, 0, 0, 1, 0, F_SKIP, L_H1, 0),
     seg(28, K_PANEL, 0, 32, 2, 64, F_WRAP, L_H1, 8, pre_sfull(0), 0, 0, 0, FL_H1, 1),
     seg(NQ, K_PANEL, 28 - 2 * NQ, 64, 1, 64, 0, L_H1Q, 16), seg(NS, K_PANEL, 28 - 2 * NQ - 2 * NS, 64, 1, 64, 0, L_H1Q, 16),
     seg(2, K_OWN, 0, 64, 32, 0, 0, L_X, 16), seg(14, K_PANEL, 0, 64, 1, 64, 0, L_O, 16, pre_sfull(1), 0, 0, 0, FL_O, 1),
     seg(4, K_ABS, 0, 0, 1, 0, F_SKIP, L_H2, 0), seg(28, K_PANEL, 0, 32, 2, 64, F_WRAP, L_H2, 8, pre_sfull(0), 0, 0, 0, FL_H2, 1),
     seg(32, K_ABS, 0, 32, 32, 0, 0, L_H2, 8, pre_ev(EV_SENT)), seg(32, K_ABS, 0, 32, 32, 0, 0, L_H2, 8),
     seg(24, K_ABS, 0, 64, 3, 256, 0, L_HB, 16, pre_ev(EV_H)), seg(16, K_ABS, 6, 64, 2, 320, 0, L_HB, 16, pre_ev(EV_H1)), seg(16, K_ABS, 10, 64, 2, 320, 0, L_HB, 16, pre_ev(EV_H2))},
    {seg(16, K_ABS, 0, 64, 32, 0, 0, L_WMOD, 32, pre_ev(EV_GO), 4, 48), seg(16, K_ABS, 0, 64, 32, 0, 0, L_WMOD, 32, 0, 4, 64),
     seg(16, K_ABS, 0, 64, 32, 0, 0, L_WMOD, 32, 0, 4, 32), seg(16, K_ABS, 0, 64, 32, 0, 0, L_WMOD, 32, 0, 4, 80)}};

struct Pipe {
    uint32_t sb, slot, par, tok, rel;
    __device__ __forceinline__ void arm() {
        uint32_t t, a; asm volatile("mov.u32 %0, %%tid.x;" : "=r"(t));
        asm("mapa.shared::cluster.u32 %0, %1, %2;" : "=r"(a) : "r"(BAR_EMPTY(sb, 0)), "r"((t >> 5) & 1));
        tok = __shfl_sync(0xffffffffu, (t & 95u) == 0 ? a : 0, t & 31);
    }
    __device__ __forceinline__ uint32_t stage() {
        mbar_wait(BAR_FULL(sb, slot), par);
        return d16(sb) + slot * (SLOT >> 4);
    }
    __device__ __forceinline__ void release() { if (rel) asm volatile("mbarrier.arrive.shared::cluster.b64 _, [%0];" :: "r"(rel) : "memory"); rel = 0; }
    __device__ __forceinline__ void issued() {
        wg_commit(); wg_wait<1>(); release();
        if (tok) rel = tok + 8 * slot;
        if (++slot == NSLOT) { slot = 0; par ^= 1; }
    }
    __device__ __forceinline__ void drain() { wg_wait<0>(); release(); }
    __device__ __forceinline__ void at(int stage) { slot = stage % NSLOT; par = (stage / NSLOT) & 1; }
};
enum { M_QKV, M_Q0KV, M_KV, M_GU3, M_GU2 };
template <int MODE, bool ZERO, bool OWN = false>
__device__ __forceinline__ void step32(float (&a256)[128], float (&a128)[64], Pipe& p, uint32_t wg, uint32_t own = 0) {
    constexpr uint32_t KS = MODE < M_KV ? 12288 : MODE == M_KV ? 8192 : 2048, LBO = MODE <= M_KV ? 2048 : 4096;
    constexpr uint32_t O256 = 8192 + (MODE < M_KV ? 4096 : 0), O128 = 8192 + (MODE < M_KV ? 0 : 16384);
    constexpr bool W128 = MODE == M_QKV || MODE == M_GU3;
    const uint32_t st = p.stage();
    wg_fence();
#pragma unroll
    for (int k = 0; k < 2; ++k) {
        const uint64_t da = OWN ? mk_desc(own, k * 32, 16, 1024, 1) : mk_desc(st + wg * 256, k * 32, 16, 512, 2);
        const uint64_t d0 = mk_desc(st, O256 + k * KS, LBO, 1024, 1), d1 = mk_desc(st, O128 + k * KS, LBO, 1024, 1);
        if (ZERO && k == 0) { wgmma_n256_z(a256, da, d0); if (W128) wgmma_n128_z(a128, da, d1); }
        else { wgmma_n256(a256, da, d0); if (W128) wgmma_n128(a128, da, d1); if (MODE == M_Q0KV) wgmma_n64<0>(a128, da, d1); }
    }
    p.issued();
}
struct Nop { __device__ __forceinline__ void operator()() const {} };
template <bool ZERO, class F = Nop>
__device__ __forceinline__ void step64(float (&acc)[64], Pipe& p, uint32_t wg, int own = -1, F landed = F()) {
    const uint32_t st = p.stage();
    landed();
    const uint32_t sa = own >= 0 ? d16(p.sb) + OFF_STG / 16 + wg * 512 + own * 1024 : st + wg * 512;
    wg_fence();
#pragma unroll
    for (int k = 0; k < 4; ++k) {
        const uint64_t da = mk_desc(sa, k * 32, 16, 1024, 1), db = mk_desc(st, 16384 + k * 2048, 8192, 1024, 1);
        if (ZERO && k == 0) wgmma_n128_z(acc, da, db); else wgmma_n128(acc, da, db);
    }
    p.issued();
}
__device__ __forceinline__ void rename(float (&d)[64], const float (&a)[64]) {
#pragma unroll
    for (int i = 0; i < 64; ++i) asm volatile("mov.b32 %0, %1;" : "=f"(d[i]) : "f"(a[i]));
}
template <int MODE, int ST>
__device__ __forceinline__ void run_own(float (&a256)[128], float (&a128)[64], Pipe& p, uint32_t wg) {
    const uint32_t a0 = d16(p.sb) + OFF_OWN / 16 + wg * 512;
    p.at(ST);
    step32<MODE, true, true>(a256, a128, p, wg, a0);
#pragma unroll 1
    for (int i = 1; i < 4; ++i) step32<MODE, false, true>(a256, a128, p, wg, a0 + (i >> 1) * 1024 + (i & 1) * 4);
    mbar_arrive_if0(BAR_FULL(p.sb, 5), threadIdx.x & 127);
    p.drain();
    p.at(ST + 4);
    step32<MODE, false>(a256, a128, p, wg);
    p.at(ST + 6);
}
template <int LG, class Step>
__device__ __forceinline__ void run(int n, uint32_t wg, uint32_t ev, Step step) {
    const int last = LG ? (wg ? EARLY : LG) : 0;
#pragma unroll 1
    for (int part = 0; ; ++part) {
#pragma unroll 1
        for (int i = part ? last : n - last; i > 0; --i) step();
        if (part || !LG) break;
        mbar_arrive_if0(ev, threadIdx.x ^ 128);
        if (wg == 0) mbar_wait(ev, 0);
    }
}

struct LnRow { float rs0, nm0, rs1, nm1; };
__device__ __forceinline__ void publish_stats(uint4* dst, float s0, float q0, float s1, float q1, uint32_t tag) {
    st_pkt16(dst, (__float_as_uint(s0) & ~3u) | tag, __float_as_uint(s1), __float_as_uint(q0), __float_as_uint(q1));
}
__device__ __forceinline__ LnRow merge_stats(const uint4* src, uint32_t tag) {
    uint4 a, b;
    do { a = ld_pkt16(src); b = ld_pkt16(src + S_ / 2); } while (!__all_sync(0xffffffffu, (a.x & b.x & tag) != 0));
    float v[4] = {__uint_as_float(a.x) + __uint_as_float(b.x), __uint_as_float(a.y) + __uint_as_float(b.y),
                  __uint_as_float(a.z) + __uint_as_float(b.z), __uint_as_float(a.w) + __uint_as_float(b.w)};
#pragma unroll
    for (int o = 1; o < 4; o <<= 1)
#pragma unroll
        for (int i = 0; i < 4; ++i) v[i] += __shfl_xor_sync(0xffffffffu, v[i], o);
    const float m0 = v[0] * (1.f / D_), m1 = v[1] * (1.f / D_);
    const float r0 = rsq(fmaxf(fmaf(-m0, m0, v[2] * (1.f / D_)), 0.f) + 1e-5f), r1 = rsq(fmaxf(fmaf(-m1, m1, v[3] * (1.f / D_)), 0.f) + 1e-5f);
    return LnRow{r0, -m0 * r0, r1, -m1 * r1};
}
__device__ __forceinline__ void ln_norm(uint32_t (&y)[32], const float (&x)[64], const LnRow& n) {
#pragma unroll
    for (int e = 0; e < 32; ++e) {
        const float rs = (e & 1) ? n.rs1 : n.rs0, nm = (e & 1) ? n.nm1 : n.nm0;
        y[e] = pack2(fmaf(x[2 * e], rs, nm), fmaf(x[2 * e + 1], rs, nm));
    }
}
__device__ __forceinline__ void ln_emit(const uint32_t (&y)[32], const uint4 (&p)[8], uint32_t sb, uint32_t wg, const Idx& ix) {
#pragma unroll
    for (int i = 0; i < 8; ++i) {
        uint32_t r[4];
#pragma unroll
        for (int e = 0; e < 4; ++e) r[e] = hfma2_bf16(y[4 * i + e], e < 2 ? p[i].z : p[i].w, e < 2 ? p[i].x : p[i].y);
        stsm4(sb + OFF_OWN + wg * 8192 + (i >> 2) * 16384 + (ix.pan ^ ((i & 3) << 5)), r[0], r[1], r[2], r[3]);
        if (i == 3) { __syncwarp(); if (ix.lane == 0) mbar_arrive(BAR_SFULL(sb, wg * 2)); }
    }
    fence_async_smem();
    __syncwarp();
    if (ix.lane == 0) mbar_arrive(BAR_SFULL(sb, wg * 2 + 1));
    bar_sync(1 + wg, 128);
}
template <int P>
__device__ __forceinline__ void load_panel(uint32_t (&r)[32], uint32_t p) {
    IDX();
#pragma unroll
    for (int i = 4 * P; i < 4 * P + 4; ++i) ldsm4(p + (pan_addr ^ ((i & 3) << 5)), r[4 * i], r[4 * i + 1], r[4 * i + 2], r[4 * i + 3]);
}
template <int E0 = 0, int E1 = 32>
__device__ __forceinline__ void widen(float (&x)[64], const uint32_t (&r)[32], uint32_t nz) {
#pragma unroll
    for (int e = E0; e < E1; e += 2) {
        x[2 * e] = bf_lo(r[e]); x[2 * e + 1] = bf_hi(r[e]); x[2 * e + 2] = bf_lo(r[e + 1]); x[2 * e + 3] = bf_hi(r[e + 1]);
        asm volatile("{\n.reg .pred p;\nsetp.eq.u32 p, %0, 0;\n@p st.shared.v4.f32 [%0], {%1, %2, %3, %4};\n}" :: "r"(nz), "f"(x[2 * e]), "f"(x[2 * e + 1]), "f"(x[2 * e + 2]), "f"(x[2 * e + 3]));
    }
}
template <int I0 = 0, int I1 = 8>
__device__ __forceinline__ void load_table(uint4 (&t)[8], uint32_t tab) {
#pragma unroll
    for (int i = I0; i < I1; ++i) t[i] = lds128(tab + i * 64 + (threadIdx.x & 3) * 16);
}
__device__ __forceinline__ float gate_of(const uint4 (&t)[8], int e) {
    const uint4 v = t[e >> 3];
    return __uint_as_float((e & 4) ? ((e & 1) ? v.w : v.z) : ((e & 1) ? v.y : v.x));
}
__device__ __forceinline__ void tile_done(uint32_t bar, uint32_t lane, uint32_t nz) {
    __syncwarp();
    asm volatile("{\n.reg .pred p, q;\nsetp.eq.u32 p, %2, 0;\nsetp.eq.u32 q, %1, 0;\nT_LOOP:\n@q mbarrier.arrive.shared::cta.b64 _, [%0];\n@p bra T_LOOP;\n}"
        :: "r"(bar), "r"(lane), "r"(nz) : "memory");
}

__device__ __forceinline__ constexpr int glu_at(int i, int e) { return (i >> 2) * 64 + ((i >> 1) & 1) * 16 + (e >> 1) * 4 + (i & 1) * 2 + (e & 1); }
struct Raw { const float (&a)[64]; __device__ __forceinline__ float operator()(int e) const { return a[e]; } };
struct Packed {
    const uint32_t (&a)[64];
    __device__ __forceinline__ float operator()(int e) const {
        float v;
        if (e & 1) asm volatile("and.b32 %0, %1, 0xFFFF0000;" : "=f"(v) : "r"(a[e >> 1])); else asm volatile("shl.b32 %0, %1, 16;" : "=f"(v) : "r"(a[e >> 1]));
        return v;
    }
};
template <class A>
__device__ __forceinline__ void glu_tanh(float (&t)[8], A a, int i) {
#pragma unroll
    for (int e = 0; e < 8; ++e) asm volatile("tanh.approx.f32 %0, %1;" : "=f"(t[e]) : "f"(a(glu_at(i, e))));
}
template <class A>
__device__ __forceinline__ void glu_store(const float (&t)[8], A a, int i, __nv_bfloat16* dst) {
    uint32_t r[4];
#pragma unroll
    for (int c = 0; c < 4; ++c) {
        const float u0 = a(32 + glu_at(i, 2 * c)), u1 = a(33 + glu_at(i, 2 * c));
        r[c] = pack2(fmaf(t[2 * c], u0, u0), fmaf(t[2 * c + 1], u1, u1));
    }
    asm volatile("{\n.reg .pred p;\nsetp.eq.u32 p, %5, %6;\nG_LOOP:\nst.global.v4.u32 [%0], {%1, %2, %3, %4};\n@p bra G_LOOP;\n}"
        :: "l"(dst + (i & 1) * 8 * F_ + (i >> 1) * 32), "r"(r[0]), "r"(r[1]), "r"(r[2]), "r"(r[3]), "r"(blockIdx.y), "r"(1000 + i) : "memory");
}
__device__ __forceinline__ void glu_now(const float (&a)[64], __nv_bfloat16* dst) {
    float t[2][8];
#pragma unroll
    for (int i = 0; i <= 4; ++i) {
        if (i < 4) glu_tanh(t[i & 1], Raw{a}, i);
        if (i > 0) glu_store(t[(i - 1) & 1], Raw{a}, i - 1, dst);
    }
}
template <class Step>
__device__ __forceinline__ void glu_under(const uint32_t (&a)[64], __nv_bfloat16* dst, int n, Step step) {
#pragma unroll 1
    for (int it = -n; it < 16; ++it) {
        step();
        if (it >= 0 && !(it & 1)) {
#pragma unroll
            for (int i = 0; i < 8; ++i)
                if (it == 2 * i) { float t[8]; glu_tanh(t, Packed{a}, i); glu_store(t, Packed{a}, i, dst); }
        }
    }
}
__device__ __forceinline__ void pack_all(uint32_t (&d)[64], const float (&a)[128]) {
#pragma unroll
    for (int i = 0; i < 64; ++i) d[i] = pack2(a[2 * i], a[2 * i + 1]);
}

__global__ void __launch_bounds__(384, 1)
fused_block_kernel(const __grid_constant__ Ptrs pt, const __grid_constant__ Maps mp) {
    uint32_t* const g_flags = pt.mail->flags;
    uint2* const g_mod = pt.mail->mod;
    uint4* const g_st1 = pt.mail->st1;
    uint32_t* const g_par2 = pt.mail->par2;
    uint4* const g_halo = pt.mail->halo;
    const __nv_bfloat16* __restrict__ cvec = pt.c;
    if (threadIdx.x == 224) { prefetch_map(&mp.ld[L_X]); prefetch_map(&mp.wm); }
    extern __shared__ __align__(1024) uint8_t smem[];
    const uint32_t sb = smem_u32(smem) + 1024;
    const uint32_t tid = threadIdx.x, tw = tid & 127, lane = tid & 31;
    const uint32_t warp = __shfl_sync(0xffffffffu, tid >> 5, 0), wg = warp >> 2;
    uint32_t rank; asm("mov.u32 %0, %%cluster_ctarank;" : "=r"(rank));
    rank = __shfl_sync(0xffffffffu, rank, 0);
    uint32_t ep;
#define LOAD_EP() asm volatile("ld.relaxed.gpu.global.u32 %0, [%1];" : "=r"(ep) : "l"(&g_flags[FL_DONE]) : "memory")
    uint32_t smid; asm volatile("mov.u32 %0, %%smid;" : "=r"(smid));
    const int c = __shfl_sync(0xffffffffu, smid >> 1, 0);
    int grp, j;
    if (c < 32) { grp = c & 7; j = c >> 3; }
    else if (c < 60) { grp = 1 + (c - 32) % 7; j = 4 + (c - 32) / 7; }
    else if (c < 62) { grp = -1; j = (c - 60) * 2 + rank; }
    else { grp = 0; j = c - 58; }
    const bool aux = grp < 0;
    const int m = grp * 2 + rank;

    bool cluster_arrive_early = false;
    if (wg < 2) {
      LOAD_EP();
      cluster_arrive();
      if (aux) {
        if (wg == 0) {
            const uint4 cv = *(const uint4*)(cvec + tw * 8);
            sts128(sb + OFF_STG + (tw >> 3) * 1024 + (tw & 7) * 16, pack2(silu_(bf_lo(cv.x)), silu_(bf_hi(cv.x))), pack2(silu_(bf_lo(cv.y)), silu_(bf_hi(cv.y))),
                   pack2(silu_(bf_lo(cv.z)), silu_(bf_hi(cv.z))), pack2(silu_(bf_lo(cv.w)), silu_(bf_hi(cv.w))));
            fence_async_smem();
        }
        cluster_wait();
        ep = __shfl_sync(0xffffffffu, ep, 0) / NCTA + 1;
        if (wg == 0) {
            if (tw == 0) {
                uint32_t n = 0;
                while (!(ld_pkt16(pt.mail->mod1 + 256).x & (1 + (ep & 1)))) { SPIN_GUARD(n); __nanosleep(200); }
                mbar_arrive(BAR_ONE(sb, EV_GO));
            }
            bar_sync(1, 128);
            Ring r{0, 0};
#pragma unroll 1
            for (int p = 0; p < 4; ++p) {
                float acc[128];
#pragma unroll
                for (int i = 0; i < 128; ++i) acc[i] = 0.f;
                uint32_t prev = 0;
#pragma unroll 1
                for (int kc = 0; kc < 16; ++kc) {
                    mbar_wait(BAR_FULL(sb, r.slot), r.par);
                    wg_fence();
#pragma unroll
                    for (int k = 0; k < 4; ++k)
                        wgmma_n256(acc, mk_desc(d16(sb) + kc * 64, OFF_STG + k * 32, 16, 0, 1), mk_desc(d16(sb) + r.slot * (SLOT >> 4), k * 2048, 8192, 1024, 1));
                    wg_commit();
                    wg_wait<1>();
                    if (kc > 0 && tw == 0) mbar_arrive(BAR_EMPTY(sb, prev));
                    prev = r.slot;
                    r.next();
                }
                wg_wait<0>();
                if (tw == 0) mbar_arrive(BAR_EMPTY(sb, prev));
                if (tw < 4) {
#pragma unroll
                    for (int jn = 0; jn < 32; ++jn) sts32(sb + OFF_TAB + (jn * 4 + tw) * 4, pack2(acc[jn * 4], acc[jn * 4 + 1]));
                }
                bar_sync(1, 128);
                const int vec = p == 0 ? 3 : p == 1 ? 4 : p == 2 ? 2 : 5, blk = (vec - 2) * 4 + j;
                const uint32_t val = lds32(sb + OFF_TAB + tw * 4);
                if (vec == 2 || vec == 5) st_pkt(g_mod + (8 + blk) * 128 + tw, val, ep);
                else {
                    const float one = vec == 4 ? 1.f : 0.f;
                    g_par2[((blk & 3) * 16 + (tw >> 3)) * 16 + (tw & 3) * 4 + (vec - 3) * 2 + ((tw >> 2) & 1)] =
                        pack2(0.5f * bf_round(one + bf_lo(val)), 0.5f * bf_round(one + bf_hi(val)));
                }
                bar_sync(1, 128);
                if (tw == 0 && (vec == 3 || vec == 4)) asm volatile("red.release.gpu.global.add.u32 [%0], 1;" :: "l"(&g_flags[FL_LN2]) : "memory");
            }
        }
      } else {
        Pipe pp{sb, 0, 0, 0, 0};
        pp.arm();
        {
            IDX();
            uint4* const st1 = g_st1 + m * 64 + warp * 8 + g8;
            if ((WARM & 1) && q4 == (g8 >> 1)) st_pkt16(st1 + j * (S_ / 2), 0, 0, 0, 0);
            cluster_wait();
            uint32_t xr[32];
            if (warp == 0) TX(0);
            mbar_wait(BAR_ONE(sb, EV_X), 0);
            if (warp == 0) TX(1);
            float sm[4] = {0.f, 0.f, 0.f, 0.f}, g0[4] = {0.f, 0.f, 0.f, 0.f}, g1[4] = {0.f, 0.f, 0.f, 0.f};
#pragma unroll
            for (int i = 0; i < 8; ++i) {
                ldsm4(sb + OFF_STG + wg * 8192 + (i >> 2) * 16384 + (pan_addr ^ ((i & 3) << 5)), xr[4 * i], xr[4 * i + 1], xr[4 * i + 2], xr[4 * i + 3]);
                mma16816(sm, xr[4 * i], xr[4 * i + 1], xr[4 * i + 2], xr[4 * i + 3], 0x3F803F80u, 0x3F803F80u);
                mma16816(g0, xr[4 * i], xr[4 * i + 1], xr[4 * i + 2], xr[4 * i + 3], xr[4 * i], xr[4 * i + 2]);
                mma16816(g1, xr[4 * i], xr[4 * i + 1], xr[4 * i + 2], xr[4 * i + 3], xr[4 * i + 1], xr[4 * i + 3]);
            }
            if (q4 == (g8 >> 1))
                publish_stats(st1 + j * (S_ / 2), sm[0], (g8 & 1) ? g0[1] : g0[0], sm[2], (g8 & 1) ? g1[3] : g1[2], 1);
            if (warp == 0) TX(2);
            float xf[64];
            widen(xf, xr, sb);
            mbar_wait(BAR_ONE(sb, EVS), 0);
            const LnRow n1 = merge_stats(st1 + q4 * S_, 1);
            if (warp == 0) TX(5);
            ln_norm(xr, xf, n1);
            ep = __shfl_sync(0xffffffffu, ep, 0) / NCTA + 1;
            asm volatile("setmaxnreg.inc.sync.aligned.u32 %0;" :: "n"(RC));
            mbar_wait(BAR_ONE(sb, EV_PAR), 0);
            if (warp == 0) TX(6);
            uint4 par[8];
            load_table(par, sb + OFF_PAR);
            ln_emit(xr, par, sb, wg, ix);
            TW(0);
        }
        {
            float qa[64];
            uint32_t kl[16], kh[16], kp[16];
            uint32_t v0[32], v1[32];
            {
                float kv[128];
                float q1[64], q2[64];
                run_own<M_QKV, 0>(kv, q1, pp, wg);
                run<0>(27 - 2 * NS - 2 * NQ, wg, 0, [&] { step32<M_QKV, false>(kv, q1, pp, wg); });
                pp.drain();
                rename(q2, q1);
                run<0>(2 * NS, wg, 0, [&] { step32<M_Q0KV, false>(kv, q2, pp, wg); });
                run<LAGQ>(2 * NQ, wg, BAR_ONE(sb, EV_LAG0), [&] { step32<M_KV, false>(kv, q2, pp, wg); });
                pp.drain();
                rename(qa, q2);
                TW(1);
                IDX();
#pragma unroll
                for (int t = 0; t < 16; ++t) v1[(t >> 1) * 4 + 2 + (t & 1)] = movm(pack2(kv[66 + 4 * t], kv[67 + 4 * t]));
#pragma unroll
                for (int t = 0; t < 16; ++t) {
                    kl[t] = pack2(kv[4 * t], kv[4 * t + 1]); kh[t] = pack2(kv[4 * t + 2], kv[4 * t + 3]);
                    v1[(t >> 1) * 4 + (t & 1)] = pack2(kv[64 + 4 * t], kv[65 + 4 * t]);
                }
                if (w4 < 3) {
                    const uint32_t dst = sb + OFF_STG + wg * 8192 + (w4 >> 1) * 16384 + (w4 & 1) * 4096;
#pragma unroll
                    for (int i = 0; i < 4; ++i) sts128(dst + i * 512 + lane * 16, kh[4 * i], kh[4 * i + 1], kh[4 * i + 2], kh[4 * i + 3]);
#pragma unroll
                    for (int i = 0; i < 8; ++i) sts64(dst + 2048 + i * 256 + lane * 8, v1[4 * i + 2], v1[4 * i + 3]);
                } else if (m < 15) {
                    uint4* const dst = g_halo + (m * 8 + j) * 512 + wg * 256;
#pragma unroll
                    for (int i = 0; i < 4; ++i) { if (!kh[4 * i]) kh[4 * i] = 0x8000u; st_pkt16(dst + i * 32 + lane, kh[4 * i], kh[4 * i + 1], kh[4 * i + 2], kh[4 * i + 3]); }
#pragma unroll
                    for (int i = 0; i < 8; ++i) { if (!v1[4 * i + 2]) v1[4 * i + 2] = 0x8000u; st_pkt((uint2*)(dst + 128) + i * 32 + lane, v1[4 * i + 2], v1[4 * i + 3]); }
                }
                TW(2);
            }
            pp.at(ST_Q);
#pragma unroll 1
            for (int it = 0; it < QA; ++it) step64<false>(qa, pp, wg);
            IDX();
            uint4* const halo = g_halo + ((m - 1) * 8 + j) * 512 + wg * 256;
            auto fetch_halo = [&] {
#pragma unroll
                for (int i = 0; i < 4; ++i) {
                    const uint4 t = m > 0 ? ld_pkt16(halo + i * 32 + lane) : make_uint4(0, 0, 0, 0);
                    kp[4 * i] = t.x; kp[4 * i + 1] = t.y; kp[4 * i + 2] = t.z; kp[4 * i + 3] = t.w;
                }
#pragma unroll
                for (int i = 0; i < 8; ++i) {
                    const uint2 t = m > 0 ? ld_pkt((const uint2*)(halo + 128) + i * 32 + lane) : make_uint2(0, 0);
                    v0[4 * i] = t.x; v0[4 * i + 1] = t.y;
                }
            };
            bar_sync(1 + wg, 128);
#pragma unroll
            for (int t = 0; t < 16; ++t) v0[(t >> 1) * 4 + 2 + (t & 1)] = v1[(t >> 1) * 4 + (t & 1)] = movm(v1[(t >> 1) * 4 + (t & 1)]);
            if (w4 == 0) fetch_halo();
            else {
                const uint32_t src = sb + OFF_STG + wg * 8192 + ((w4 - 1) >> 1) * 16384 + ((w4 - 1) & 1) * 4096;
#pragma unroll
                for (int i = 0; i < 4; ++i) { const uint4 t = lds128(src + i * 512 + lane * 16); kp[4 * i] = t.x; kp[4 * i + 1] = t.y; kp[4 * i + 2] = t.z; kp[4 * i + 3] = t.w; }
#pragma unroll
                for (int i = 0; i < 8; ++i) { const uint2 t = lds64(src + 2048 + i * 256 + lane * 8); v0[4 * i] = t.x; v0[4 * i + 1] = t.y; }
            }
            TW(18);
            pp.at(ST_Q + QA);
#pragma unroll 1
            for (int it = QA; it < NQ; ++it) step64<false>(qa, pp, wg);
            bar_sync(1 + wg, 128);
            if (w4 == 0 && m > 0) {
                while (true) {
                    bool ok = true;
#pragma unroll
                    for (int i = 0; i < 8; ++i) ok = ok && v0[4 * i] != 0 && kp[4 * (i & 3)] != 0;
                    if (__all_sync(0xffffffffu, ok)) break;
                    fetch_halo();
                }
            }
            pp.drain();
            float qb[64];
            rename(qb, qa);
            TW(3);
            const bool lo0 = q4 * 2 > g8, lo1 = q4 * 2 + 1 > g8;
            const bool nopast = m == 0 && w4 == 0;
            const uint32_t lomask = (lo0 ? 0xFFFFu : 0u) | (lo1 ? 0xFFFF0000u : 0u);
            const float sl2 = 0.17677669529663687f * 1.4426950408889634f;
            const uint32_t oa = wg * 8192 + (w4 * 16 + (lane & 7)) * 128 + (((lane >> 3) ^ (lane & 7)) << 4);
#pragma unroll
            for (int hp = 0; hp < 2; ++hp) {
                if (hp) {
                    bar_sync(3, 256);
#pragma unroll 1
                    for (int it = 0; it < NS; ++it) {
                        pp.slot = (SWEEP >> (4 * it)) & 7; pp.par = (SWEEP >> (4 * it + 3)) & 1;
                        const uint32_t st = pp.stage();
                        wg_fence();
#pragma unroll
                        for (int k = 0; k < 4; ++k) wgmma_n64<32>(qb, mk_desc(st + wg * 512, k * 32, 16, 1024, 1), mk_desc(st, 24576 + k * 2048, 8192, 1024, 1));
                        pp.issued();
                    }
                    pp.drain();
                    TW(4);
                }
                float e0[4], e1[4], mx[4], sum[4];
#pragma unroll
                for (int hh = 0; hh < 2; ++hh) {
                    const int h = 2 * hp + hh;
                    uint32_t qf[8];
                    float s[3][4];
#pragma unroll
                    for (int i = 0; i < 8; ++i) qf[i] = pack2(qb[16 * h + 2 * i], qb[16 * h + 2 * i + 1]);
#pragma unroll
                    for (int nt = 0; nt < 3; ++nt) {
                        const uint32_t (&kk)[16] = nt == 0 ? kp : nt == 1 ? kl : kh;
                        s[nt][0] = s[nt][1] = s[nt][2] = s[nt][3] = 0.f;
                        mma16816(s[nt], qf[0], qf[1], qf[2], qf[3], kk[4 * h], kk[4 * h + 1]);
                        mma16816(s[nt], qf[4], qf[5], qf[6], qf[7], kk[4 * h + 2], kk[4 * h + 3]);
                    }
#pragma unroll
                    for (int hf = 0; hf < 2; ++hf) {
                        e0[2 * hh + hf] = lo0 ? ((hf == 0 && nopast) ? -INFINITY : s[hf][hf * 2]) : s[hf + 1][hf * 2];
                        e1[2 * hh + hf] = lo1 ? ((hf == 0 && nopast) ? -INFINITY : s[hf][hf * 2 + 1]) : s[hf + 1][hf * 2 + 1];
                        mx[2 * hh + hf] = fmaxf(e0[2 * hh + hf], e1[2 * hh + hf]);
                    }
                }
#pragma unroll
                for (int o = 1; o < 4; o <<= 1)
#pragma unroll
                    for (int u = 0; u < 4; ++u) mx[u] = fmaxf(mx[u], __shfl_xor_sync(0xffffffffu, mx[u], o));
#pragma unroll
                for (int u = 0; u < 4; ++u) {
                    const float c = -mx[u] * sl2;
                    e0[u] = ex2(fmaf(e0[u], sl2, c)); e1[u] = ex2(fmaf(e1[u], sl2, c));
                    sum[u] = e0[u] + e1[u];
                }
#pragma unroll
                for (int o = 1; o < 4; o <<= 1)
#pragma unroll
                    for (int u = 0; u < 4; ++u) sum[u] += __shfl_xor_sync(0xffffffffu, sum[u], o);
#pragma unroll
                for (int u = 0; u < 4; ++u) {
                    const int h = 2 * hp + (u >> 1), hf = u & 1;
                    const uint32_t (&vv)[32] = hf ? v1 : v0;
                    const float iv = rcp(sum[u]);
                    const uint32_t pr = pack2(e0[u] * iv, e1[u] * iv);
                    float o[2][4];
#pragma unroll
                    for (int t = 0; t < 2; ++t) {
                        o[t][0] = o[t][1] = o[t][2] = o[t][3] = 0.f;
                        mma16816(o[t], vv[8 * h + 4 * t], vv[8 * h + 4 * t + 1], vv[8 * h + 4 * t + 2], vv[8 * h + 4 * t + 3], pr & lomask, pr & ~lomask);
                    }
                    stsm4t(sb + OFF_STG + hp * 16384 + (oa ^ ((h & 1) << 6)) + hf * 1024, pack2(o[0][0], o[0][1]), pack2(o[0][2], o[0][3]), pack2(o[1][0], o[1][1]), pack2(o[1][2], o[1][3]));
                }
                __syncwarp();
                if (lane == 0) mbar_arrive(BAR_SFULL(sb, wg * 2 + hp));
                if (!hp) TW(19);
            }
            TW(5);
        }
        {
            float acc[64], xf[64];
            uint4 gt[8], par[8];
            fence_async_smem();
            bar_sync(3, 256);
            uint32_t xr[32];
            pp.at(ST_WO);
            step64<true>(acc, pp, wg, 0);
            pp.rel = 0;
            step64<false>(acc, pp, wg, 1, [&] {
                load_panel<0>(xr, sb + ST_WO % NSLOT * SLOT + wg * 8192);
                load_panel<1>(xr, sb + (ST_WO + 1) % NSLOT * SLOT + wg * 8192);
            });
            pp.rel = 0;
            step64<false>(acc, pp, wg);
            fence_async_smem();
            bar_sync(1 + wg, 128);
            if (pp.tok) {
#pragma unroll
                for (int i = 0; i < 2; ++i) asm volatile("mbarrier.arrive.shared::cluster.b64 _, [%0];" :: "r"(pp.tok + 8 * ((ST_WO + i) % NSLOT)) : "memory");
            }
            widen<0, 16>(xf, xr, ep);
            pp.at(ST_WO + 3);
            step64<false>(acc, pp, wg);
            widen<16, 32>(xf, xr, ep);
            if ((tid & 96) == 0 && m > 0) {
#pragma unroll
                for (int i = 0; i < 8; ++i) (g_halo + ((m - 1) * 8 + j) * 512 + wg * 256 + lane)[i * 32] = make_uint4(0, 0, 0, 0);
            }
            uint4* const st2 = g_st1 + __shfl_sync(0xffffffffu, m * 64 + (tid >> 2), lane);
            pp.at(ST_WO + 4);
            run<LAGW>(12, wg, BAR_ONE(sb, EV_LAG4), [&] { step64<false>(acc, pp, wg); });
            mbar_wait(BAR_ONE(sb, EV_GA), 0);
            load_table(gt, sb + OFF_TAB);
            IDX();
            pp.drain();
            TW(6);
            float su[4] = {0.f, 0.f, 0.f, 0.f}, sq[4] = {0.f, 0.f, 0.f, 0.f};
#pragma unroll
            for (int e = 0; e < 64; ++e) {
                xf[e] = fmaf(gate_of(gt, e), acc[e], xf[e]);
                su[e & 3] += xf[e]; sq[e & 3] = fmaf(xf[e], xf[e], sq[e & 3]);
            }
            {
                float v[4] = {su[0] + su[1], sq[0] + sq[1], su[2] + su[3], sq[2] + sq[3]};
#pragma unroll
                for (int o = 1; o < 4; o <<= 1)
#pragma unroll
                    for (int i = 0; i < 4; ++i) v[i] += __shfl_xor_sync(0xffffffffu, v[i], o);
                if (q4 == 0) publish_stats(st2 + j * (S_ / 2), v[0], v[1], v[2], v[3], 2);
            }
            TW(7);
#pragma unroll
            for (int i = 0; i < 8; ++i)
                stsm4(sb + OFF_STG + wg * 8192 + (i >> 2) * 16384 + (pan_addr ^ ((i & 3) << 5)), pack2(xf[8 * i], xf[8 * i + 1]), pack2(xf[8 * i + 2], xf[8 * i + 3]),
                      pack2(xf[8 * i + 4], xf[8 * i + 5]), pack2(xf[8 * i + 6], xf[8 * i + 7]));
            load_table(par, sb + OFF_PAR);
            mbar_wait(BAR_EMPTY(sb, (ST_GU - 1) % NSLOT), ((ST_GU - 1) / NSLOT) & 1);
            if (warp == 0) TX(8);
            const LnRow n2 = merge_stats(st2 + q4 * S_, 2);
            TW(8);
            ln_norm(xr, xf, n2);
            ln_emit(xr, par, sb, wg, ix);
            TW(9);
        }
        {
            auto h_at = [&](int col) { IDX(); return pt.hb + (m * 128 + warp * 16 + g8) * F_ + j * 448 + col + q4 * 8; };
            uint32_t gu[64];
            {
                float a256[128], a128[64];
                run_own<M_GU3, ST_GU>(a256, a128, pp, wg);
                run<LAG>(27, wg, BAR_ONE(sb, EV_LAG1), [&] { step32<M_GU3, false>(a256, a128, pp, wg); });
                __nv_bfloat16* const dst = h_at(128);
                pp.drain();
                TW(10);
                glu_now(a128, dst);
                pack_all(gu, a256);
                TW(11);
            }
#pragma unroll 1
            for (int p = 0; p < 2; ++p) {
                float b256[128], none[64];
                pp.at(p ? ST_G1 + 32 : ST_G1);
                step32<M_GU2, true>(b256, none, pp, wg);
                glu_under(gu, h_at(p * 192), GW + wg, [&] { step32<M_GU2, false>(b256, none, pp, wg); });
                mbar_arrive_if0(BAR_ONE(sb, EV_HB), lane);
                run<LAGS>(15 - GW - wg, wg, BAR_ONE(sb, EV_LAG2 + p), [&] { step32<M_GU2, false>(b256, none, pp, wg); });
                pp.drain();
                TW(12 + 2 * p);
                pack_all(gu, b256);
                TW(13 + 2 * p);
            }
            float acc[64], xf[64];
            uint4 gt[8];
            pp.at(ST_G1 + 64);
            step64<true>(acc, pp, wg);
            glu_under(gu, h_at(320), GD + wg, [&] { step64<false>(acc, pp, wg); });
            mbar_arrive_if0(BAR_ONE(sb, EV_HB), lane);
            uint32_t x1[32];
#pragma unroll
            for (int i = 0; i < 32; ++i) asm volatile("" : "=r"(x1[i]), "=f"(xf[2 * i]), "=f"(xf[2 * i + 1]));
#pragma unroll
            for (int i = 0; i < 8; ++i) asm volatile("" : "=r"(gt[i].x), "=r"(gt[i].y), "=r"(gt[i].z), "=r"(gt[i].w));
            mbar_wait(BAR_ONE(sb, EV_GB), 0);
#pragma unroll 1
            for (int it = 0; it < 16; ++it) {
                step64<false>(acc, pp, wg, -1, [&] {
                    if (it == 0) load_panel<0>(x1, sb + OFF_STG + wg * 8192);
                    if (it == 2) load_panel<1>(x1, sb + OFF_STG + wg * 8192 + 16384);
                    if (it == 12) load_table<0, 4>(gt, sb + OFF_TAB + 512);
                    if (it == 14) load_table<4, 8>(gt, sb + OFF_TAB + 512);
                });
                if (it == 4) widen<0, 8>(xf, x1, ep);
                if (it == 6) widen<8, 16>(xf, x1, ep);
                if (it == 8) widen<16, 24>(xf, x1, ep);
                if (it == 10) widen<24, 32>(xf, x1, ep);
            }
            run<LAGD>(23 - GD - wg, wg, BAR_ONE(sb, EV_LAG5), [&] { step64<false>(acc, pp, wg); });
            cluster_arrive();
            IDX();
            wg_wait<0>();
            TW(16);
#pragma unroll
            for (int p = 0; p < 2; ++p) {
#pragma unroll
                for (int i = 4 * p; i < 4 * p + 4; ++i) {
                    uint32_t r[4];
#pragma unroll
                    for (int e = 0; e < 4; ++e)
                        r[e] = pack2(fmaf(gate_of(gt, 8 * i + 2 * e), acc[8 * i + 2 * e], xf[8 * i + 2 * e]), fmaf(gate_of(gt, 8 * i + 2 * e + 1), acc[8 * i + 2 * e + 1], xf[8 * i + 2 * e + 1]));
                    stsm4(sb + OFF_STG + wg * 8192 + p * 16384 + (pan_addr ^ ((i & 3) << 5)), r[0], r[1], r[2], r[3]);
                }
                tile_done(BAR_SFULL(sb, wg * 2 + p), lane, ep);
            }
            TW(17);
        }
      }
    } else {
        if (elect_one()) {
            if (warp == 8) {
                mbar_init(BAR_ONE(sb, EV_X), 1);
                if (!aux) {
                    mbar_expect_tx(BAR_ONE(sb, EV_X), 32768);
#pragma unroll
                    for (int i = 0; i < 2; ++i) tma_load4(sb + OFF_STG + i * 16384, &mp.ld[L_X], j * 128 + i * 64, m * 64, 0, BAR_ONE(sb, EV_X));
                }
#pragma unroll
                for (int i = 0; i < 2; ++i) {
                    mbar_init(BAR_ONE(sb, EV_WIN + i), 1);
                    if (!aux) {
                        mbar_expect_tx(BAR_ONE(sb, EV_WIN + i), 16384);
                        tma_load(sb + OFF_OWN + i * 16384, &mp.wm, (m * 2 + (j >> 2)) * 64, (j & 3) * 256 + i * 128, BAR_ONE(sb, EV_WIN + i));
                    }
                }
                prefetch_map(&mp.ld[aux ? L_WMOD : L_WQKV]);
            } else if (warp < 11) {
#pragma unroll
                for (int i = 0; i < 3; ++i) mbar_init(BAR_FULL(sb, (warp - 9) * 3 + i), aux ? 1 : 2);
#pragma unroll
                for (int i = 0; i < 2; ++i) mbar_init(BAR_SFULL(sb, (warp - 9) * 2 + i), 4);
#pragma unroll
                for (int i = 0; i < 3; ++i) mbar_init(BAR_EMPTY(sb, (warp - 9) * 3 + i), aux ? 1 : 4);
            } else {
#pragma unroll
                for (int i = EV_GA; i < EV_COUNT; ++i) mbar_init(BAR_ONE(sb, i), i == EV_HB ? 8 : i == EV_GA ? 2 : 1);
            }
            asm volatile("fence.mbarrier_init.release.cluster;" ::: "memory");
        }
        __syncwarp();
        LOAD_EP();
        uint4 sg = make_uint4(0, 0, 0, 0);
        const uint4 cv = *(const uint4*)(cvec + (j & 3) * 256 + lane * 8);
        uint4* const modp = pt.mail->mod1 + (lane >> 2) * 2048 + (j & 3) * 512 + ((m * 2 + (j >> 2)) * 4 + (warp & 3)) * 4 + (lane & 3);
        if ((WARM & 2) && !aux) st_pkt16(modp, 0, 0, 0, 0);
        if (lane < NSEG) sg = g_sched[aux ? 2 : warp == 11][lane];
        cluster_arrive();
        cluster_wait();
        const bool el = elect_one();
        const int kown = j * 128;
        if (!aux) {
            if (warp == 8 && el) {
#pragma unroll
                for (int i = 0; i < NB0; ++i) {
                    mbar_arrive(BAR_FULL(sb, i));
                    mbar_expect_tx(BAR_FULL(sb, i), 24576);
                    tma_load5_mc(sb + i * SLOT + 8192 + rank * 12288, &mp.ld[L_WQKV], 0, kown + i * 32 + rank * 16, 2 * j, 0, 0, BAR_FULL(sb, i));
                }
            }
            const uint32_t s0 = pack2(silu_(bf_lo(cv.x)), silu_(bf_hi(cv.x))), s1 = pack2(silu_(bf_lo(cv.y)), silu_(bf_hi(cv.y))),
                           s2 = pack2(silu_(bf_lo(cv.z)), silu_(bf_hi(cv.z))), s3 = pack2(silu_(bf_lo(cv.w)), silu_(bf_hi(cv.w)));
#pragma unroll
            for (int i = 0; i < 2; ++i) { const uint32_t row = (warp & 3) + 4 * i; sts128(sb + 4 * SLOT + (lane >> 3) * 1024 + row * 128 + (((lane & 7) ^ row) << 4), s0, s1, s2, s3); }
            fence_async_smem();
            bar_sync(4, 128);
            ep = __shfl_sync(0xffffffffu, ep, 0) / NCTA + 1;
            float acc[32];
#pragma unroll
            for (int i = 0; i < 32; ++i) acc[i] = 0.f;
#pragma unroll 1
            for (int h = 0; h < 2; ++h) {
                mbar_wait(BAR_ONE(sb, EV_WIN + h), 0);
                if (warp == 11) TX(3);
                wg_fence();
#pragma unroll
                for (int k = 0; k < 8; ++k)
                    wgmma_n64<0>(acc, mk_desc(d16(sb) + h * 128, 4 * SLOT + (k >> 2) * 1024 + (k & 3) * 32, 16, 0, 1), mk_desc(d16(sb) + h * 1024, OFF_OWN + k * 2048, 8192, 1024, 1));
                wg_commit();
            }
            wg_wait<0>();
            const uint32_t i = warp & 3;
            auto pick = [&](int e) { return __float_as_uint(i & 2 ? (i & 1 ? acc[24 + e] : acc[16 + e]) : (i & 1 ? acc[8 + e] : acc[e])); };
            st_pkt16(modp, (pick(0) & ~3u) | (1 + (ep & 1)), pick(1), pick(4), pick(5));
            if (warp == 11) TX(4);
        } else ep = __shfl_sync(0xffffffffu, ep, 0) / NCTA + 1;
        asm volatile("setmaxnreg.dec.sync.aligned.u32 %0;" :: "n"(504 - 2 * RC));

        if (warp == 8 || (warp == 11 && !aux)) {
            const bool act = warp == 11;
            if (act) {
                const uint4* pk = pt.mail->mod1 + grp * 2048 + j * 32 + lane;
                uint4 a[8];
                while (true) {
                    uint32_t t = 1 + (ep & 1);
#pragma unroll
                    for (int i = 0; i < 8; ++i) { a[i] = ld_pkt16(pk + i * 256); t &= a[i].x; }
                    if (__all_sync(0xffffffffu, t != 0)) break;
                }
                uint32_t r[4];
#pragma unroll
                for (int v = 0; v < 2; ++v) {
                    auto sum = [&](uint32_t uint4::*f) { return bf_round((__uint_as_float(a[v].*f) + __uint_as_float(a[2 + v].*f)) + (__uint_as_float(a[4 + v].*f) + __uint_as_float(a[6 + v].*f))) + v; };
                    r[2 * v] = pack2(sum(&uint4::x), sum(&uint4::y)); r[2 * v + 1] = pack2(sum(&uint4::z), sum(&uint4::w));
                }
                sts128(sb + OFF_PAR + lane * 16, r[0], r[1], r[2], r[3]);
                __syncwarp();
                if (el) mbar_arrive(BAR_ONE(sb, EV_PAR));
                if (warp == 11) TX(7);
            }
            {
                const uint32_t split = sg.z >> 20, bytes = (sg.z & 63) << 10;
                const uint32_t dst = split ? (split == 3 ? 16384 : 8192) + rank * (split == 2 ? 4096 : bytes >> 1) : 0;
                const uint32_t blk = ((sg.z >> 8) & 15) * j + ((sg.z >> 12) & 255) + (split == 3 ? rank : 0);
                if (split == 2) sg.x += rank << 24;
                if (split == 1) sg.y |= rank << 12;
                sg.z = dst | blk << 16 | (sg.z & 63) << 24;
            }
            Ring r{0, 1};
#pragma unroll 1
            for (int s = 0; ; ++s) {
                const uint32_t x = __shfl_sync(0xffffffffu, sg.x, s), y = __shfl_sync(0xffffffffu, sg.y, s), z = __shfl_sync(0xffffffffu, sg.z, s), w = __shfl_sync(0xffffffffu, sg.w, s);
                const uint32_t nx = __shfl_sync(0xffffffffu, sg.x, s + 1);
                if (!x) break;
                if (el) prefetch_map(&mp.ld[nx >> 24]);
                const CUtensorMap* const tm = &mp.ld[x >> 24];
                const uint32_t n = x & 255, blk = (z >> 16) & 255, bytes = (z >> 24) << 10, cnt = w >> 24, base = sb + (z & 0xFFFF);
                if (x & (F_SKIP << 16)) {
                    r.slot += n;
                    if (r.slot >= NSLOT) { r.slot -= NSLOT; r.par ^= 1; }
                    continue;
                }
                uint32_t kl;
                {
                    const uint32_t a = (y >> 2) & 63, step = (y >> 16) & 255, ch = a + lane * (step >> 5), u = ch >> 1, q = u < 7 ? u : u - 7;
                    kl = (y & 3) == K_PANEL ? (q + (q >= j)) * 128 + (u < 7 ? 0 : 64) + (ch & 1) * 32
                                            : ch * 32 + ((lane * ((x >> 8) & 255)) >> 7) * (y >> 24) * 64 + ((y & 3) == K_OWN ? kown : 0);
                    kl += (y >> 8) & 16;
                }
                uint32_t wrap = NSLOT - ((x >> 16) & F_WRAP);
                auto acquire = [&](uint32_t& st, uint32_t& fb) {
                    mbar_wait(BAR_EMPTY(sb, r.slot), r.par);
                    st = base + r.slot * SLOT; fb = BAR_FULL(sb, r.slot);
                    if (++r.slot == wrap) { r.slot = 0; r.par ^= 1; }
                    wrap = NSLOT;
                };
                uint32_t st, fb;
                if (w & 0xFFFF) { mbar_wait(sb + OFF_BAR + (w & 0xFFF8), w & 1); fence_async_global(); }
                if (act | aux) {
                    const uint32_t* const fl = g_flags + m * 64 + ((w >> 16) & 255) + ((kl >> 6) & 15);
                    const int row = (x >> 24) == L_X ? m * 64 : m * 128;
                    const uint32_t trig = (x & (F_WRAP << 16)) ? 5 : (x >> 24) == L_O ? TRIGO : 255;
                    uint32_t ready = cnt ? 0 : ~0u;
#pragma unroll 1
                    for (uint32_t i = 0; i < n; ++i) {
                        const uint32_t k = __shfl_sync(0xffffffffu, kl, i);
                        while (!((ready >> i) & 1)) {
                            uint32_t v; asm volatile("ld.relaxed.gpu.global.u32 %0, [%1];" : "=r"(v) : "l"(fl) : "memory");
                            ready = __ballot_sync(0xffffffffu, (int32_t)(v - ep) >= 0);
                            fence_async_global();
                        }
                        acquire(st, fb);
                        if (el) { mbar_expect_tx(fb, bytes); tma_load4(st, tm, aux ? 0 : k, aux ? k : row, aux ? blk : 0, fb); }
                        if (el && i == trig) mbar_arrive(BAR_ONE(sb, EV_SEC));
                    }
                } else {
                    const bool twice = el && (x & (F_TWICE << 16)), wd = (x >> 24) == L_WD;
                    const uint32_t more = (x >> 25) == L_WG / 2 ? (bytes >> 13) - 1 : 0;
#pragma unroll 1
                    for (uint32_t i = 0; i < n; ++i) {
                        const uint32_t k = __shfl_sync(0xffffffffu, kl, i);
                        acquire(st, fb);
                        if (twice) mbar_arrive(fb);
                        if (el) { mbar_expect_tx(fb, bytes); tma_load5_mc(st, tm, wd ? blk * 64 : 0, wd ? 0 : k, wd ? 0 : blk, (x >> 24) == L_WKV, wd ? k >> 5 : 0, fb); }
                        if (more && el) tma_load5_mc(st + 8192, tm, 0, k, blk + 1, 0, 0, fb);
                        if (more > 1 && el) tma_load5_mc(st + 16384, tm, 0, k, blk + 2, 0, 0, fb);
                    }
                }
            }
        } else if (!aux) {
            const uint32_t w = warp - 9;
            const int row0 = m * 128 + w * 64;
            const uint32_t stg = sb + OFF_STG + w * 8192;
            uint32_t par = 0;
            auto store = [&](const CUtensorMap* tm, int col, uint32_t b, bool nat = false) {
                mbar_wait_b(BAR_SFULL(sb, w * 2 + b), par);
                if (el) {
                    fence_async_smem();
                    tma_store(tm, (nat ? w * D_ + col : col) + b * 64, nat ? m * 64 : row0, stg + b * 16384);
                    bulk_commit();
                }
                par ^= b;
            };
            uint32_t bpar = 0;
            auto flag_landed = [&](uint32_t* f, const CUtensorMap* tm, int col, int row, int n, int sh, uint32_t rest) {
                if (rest) __nanosleep(rest);
                if (el) mbar_expect_tx(BAR_ONE(sb, EV_BACK + w), n * 512);
#pragma unroll 1
                for (int i = 0; i < n; ++i) if (el) tma_load(sb + OFF_JUNK, tm, col + (i >> sh) * 64, row + (i & ((1 << sh) - 1)) * 32, BAR_ONE(sb, EV_BACK + w));
                mbar_wait_b(BAR_ONE(sb, EV_BACK + w), bpar);
                bpar ^= 1;
                if (el) flag_add(f);
            };
            auto send = [&](const CUtensorMap* tm, uint32_t src, bool ring, int f) {
#pragma unroll 1
                for (uint32_t p = 0; p < 2; ++p) {
                    if (p && (ring || TRIGO < 255)) mbar_wait_b(BAR_ONE(sb, EV_SEC), TRIGO < 255 ? par : f >> 5);
#pragma unroll
                    for (int g = 1; g >= 0; --g) {
                        mbar_wait_b(BAR_SFULL(sb, 2 * g + p), par);
                        if (el) { fence_async_smem(); tma_store(tm, kown + p * 64, m * 128 + g * 64, src + p * 16384 + g * 8192); }
                    }
                    if (el) { bulk_commit(); bulk_wait_all(); }
                    __syncwarp();
                    if (p && ring && lane < 4) asm volatile("{\n.reg .b32 r;\nmapa.shared::cluster.u32 r, %0, %1;\nmbarrier.arrive.shared::cluster.b64 _, [r];\n}" :: "r"(BAR_EMPTY(sb, 5)), "r"(lane & 1) : "memory");
                    flag_landed(g_flags + m * 64 + f + 2 * j + p, tm + 2, kown + p * 64, m * 128, 4, 2, p ? (ring ? REST1 : RESTO) : 0);
                    if (el && !p) TS(43 + (f >> 4));
                }
                par ^= 1;
            };
            auto gate = [&](int vec, int ev) {
                uint2 a, b; uint32_t n = 0;
                const uint2* src = g_mod + vec * 512 + j * 64 + (lane >> 2) * 8 + (lane & 3);
                while (true) {
                    a = ld_pkt(src); b = ld_pkt(src + 4);
                    if (__all_sync(0xffffffffu, a.y == ep && b.y == ep)) break;
                    SPIN_GUARD(n); __nanosleep(300);
                }
                sts128(sb + OFF_TAB + (ev - EV_GA) * 512 + lane * 16, a.x << 16, a.x & 0xFFFF0000u, b.x << 16, b.x & 0xFFFF0000u);
                __syncwarp();
                if (el) mbar_arrive(BAR_ONE(sb, ev));
            };
            if (lane < 6) prefetch_map(&mp.h1s + lane);
            if (w == 0) {
#pragma unroll 1
                for (int t = 0; t < 3; ++t) {
                    send(t ? &mp.os : &mp.h1s, sb + (t == 1 ? OFF_STG : OFF_OWN), t != 1, 16 * t);
                    if (t && el) mbar_arrive(BAR_ONE(sb, t == 1 ? EV_GA : EV_SENT));
                }
            } else {
                mbar_wait_b(BAR_SFULL(sb, 1), 0); mbar_wait_b(BAR_SFULL(sb, 3), 0);
                auto count = [&](int f) {
                    uint32_t v, n = 0;
                    while (true) {
                        asm volatile("ld.acquire.gpu.global.u32 %0, [%1];" : "=r"(v) : "l"(g_flags + f) : "memory");
                        if ((int32_t)(v - ep * 8) >= 0) break;
                        SPIN_GUARD(n); __nanosleep(500);
                    }
                };
                count(FL_LN2);
                const uint4 t = __ldcg((const uint4*)(g_par2 + j * 128) + lane);
                sts128(sb + OFF_PAR + lane * 16, t.x, t.y, t.z, t.w);
#pragma unroll 1
                for (int t = 0; t < 2; ++t) gate(2 + 3 * t, EV_GA + t);
#pragma unroll 1
                for (int p = 0; p < 3; ++p) {
                    mbar_wait_b(BAR_ONE(sb, EV_HB), p & 1);
                    __nanosleep(RESTH);
                    if (el) asm volatile("red.release.gpu.global.add.u32 [%0], 1;" :: "l"(g_flags + m * 64 + FL_H + p) : "memory");
                    count(m * 64 + FL_H + p);
                    if (el) mbar_arrive(BAR_ONE(sb, EV_H + p));
                }
                par = 1;
            }
            cluster_arrive_early = true;
            cluster_arrive();
            store(&mp.out, kown, 0, true); store(&mp.out, kown, 1, true);
            if (el) bulk_wait_read();
        }
        __syncwarp();
    }
    if (aux || (wg == 2 && !cluster_arrive_early)) cluster_arrive();
    cluster_wait();
    if (tid == 0) {
        flag_add(pt.mail->flags + FL_DONE);
    }
}

typedef CUresult (*EncodeFn)(CUtensorMap*, CUtensorMapDataType, cuuint32_t, void*, const cuuint64_t*, const cuuint64_t*, const cuuint32_t*,
                             const cuuint32_t*, CUtensorMapInterleave, CUtensorMapSwizzle, CUtensorMapL2promotion, CUtensorMapFloatOOBfill);

void make_map(EncodeFn fn, CUtensorMap* m, const void* ptr, uint64_t rows, uint64_t cols, uint32_t brows, uint32_t bcols) {
    cuuint64_t dims[2] = {cols, rows}, strides[1] = {cols * 2};
    cuuint32_t box[2] = {bcols, brows}, es[2] = {1, 1};
    fn(m, CU_TENSOR_MAP_DATA_TYPE_BFLOAT16, 2, (void*)ptr, dims, strides, box, es, CU_TENSOR_MAP_INTERLEAVE_NONE,
       bcols == 64 ? CU_TENSOR_MAP_SWIZZLE_128B : bcols == 32 ? CU_TENSOR_MAP_SWIZZLE_64B : CU_TENSOR_MAP_SWIZZLE_NONE, CU_TENSOR_MAP_L2_PROMOTION_L2_256B, CU_TENSOR_MAP_FLOAT_OOB_FILL_NONE);
}
struct View { uint64_t dim[5], stride[4]; uint32_t box[5]; };
void make_view(EncodeFn fn, CUtensorMap* m, const void* ptr, uint32_t rank, const View& v) {
    cuuint64_t dims[5], strides[4];
    cuuint32_t box[5], es[5] = {1, 1, 1, 1, 1};
    for (int i = 0; i < 5; ++i) { dims[i] = v.dim[i]; box[i] = v.box[i]; if (i < 4) strides[i] = v.stride[i] * 2; }
    fn(m, CU_TENSOR_MAP_DATA_TYPE_BFLOAT16, rank, (void*)ptr, dims, strides, box, es, CU_TENSOR_MAP_INTERLEAVE_NONE,
       box[0] == 64 ? CU_TENSOR_MAP_SWIZZLE_128B : CU_TENSOR_MAP_SWIZZLE_64B, CU_TENSOR_MAP_L2_PROMOTION_L2_256B, CU_TENSOR_MAP_FLOAT_OOB_FILL_NONE);
}

}

extern "C" void kernel_launch(void* const* d_in, const int* in_sizes, int n_in, void* d_out, int out_size) {
    (void)in_sizes; (void)n_in; (void)out_size;
    void* fnp = nullptr;
    cudaDriverEntryPointQueryResult qr;
    cudaGetDriverEntryPoint("cuTensorMapEncodeTiled", &fnp, cudaEnableDefault, &qr);
    EncodeFn fn = (EncodeFn)fnp;
    void *h1, *o, *hb, *mail;
    cudaGetSymbolAddress(&h1, g_h1);
    cudaGetSymbolAddress(&mail, g_mail);
    cudaGetSymbolAddress(&o, g_o);
    cudaGetSymbolAddress(&hb, g_hb);
    Maps mp;
    auto wmap = [&](int i, const void* p, uint64_t rows, uint64_t cols, uint64_t sec, uint32_t brows, uint32_t bblk, uint32_t bsec) {
        make_view(fn, &mp.ld[i], p, i == L_WMOD ? 4 : 5, View{{64, rows, cols / sec / 64, sec, 1}, {cols, 64, cols / sec, 64}, {64, brows, bblk, bsec, 1}});
    };
    auto amap = [&](int i, const void* p, uint64_t cols, uint32_t bcols) { make_view(fn, &mp.ld[i], p, 4, View{{cols, S_, 1, 1, 1}, {cols, 64, 64, 64}, {bcols, 128, 1, 1, 1}}); };
    wmap(L_WQKV, d_in[1], D_, 3 * D_, 3, 16, 2, 3);
    wmap(L_WKV, d_in[1], D_, 3 * D_, 3, 16, 2, 2);
    wmap(L_WQ, d_in[1], D_, 3 * D_, 3, 64, 1, 1);
    wmap(L_WO, d_in[2], D_, D_, 1, 64, 1, 1);
    wmap(L_WG, d_in[4], D_, F_, 1, 32, 1, 1);
    wmap(L_WU, d_in[5], D_, F_, 1, 32, 1, 1);
    make_view(fn, &mp.ld[L_WD], d_in[6], 5, View{{D_, 2, 4, 4, F_ / 32}, {D_, 8 * D_, 2 * D_, 32 * D_}, {64, 2, 4, 4, 2}});
    wmap(L_WMOD, d_in[8], D_, 6 * D_, 1, 64, 4, 1);
    amap(L_H1, h1, D_, 32); amap(L_H1Q, h1, D_, 64); amap(L_O, o, D_, 64); amap(L_H2, o, D_, 32); amap(L_HB, hb, F_, 64);
    make_view(fn, &mp.ld[L_X], d_in[0], 4, View{{D_, S_ / 2, 2, 1, 1}, {2 * D_, D_, 64, 64}, {64, 64, 2, 1, 1}});
    make_map(fn, &mp.h1s, h1, S_, D_, 64, 64);
    make_map(fn, &mp.os, o, S_, D_, 64, 64);
    make_map(fn, &mp.h1r, h1, S_, D_, 32, 8);
    make_map(fn, &mp.orr, o, S_, D_, 32, 8);
    make_map(fn, &mp.hbr, hb, S_, F_, 32, 8);
    make_map(fn, &mp.wm, d_in[8], D_, 6 * D_, 128, 64);
    make_map(fn, &mp.out, d_out, S_ / 2, 2 * D_, 64, 64);
    cudaFuncSetAttribute(fused_block_kernel, cudaFuncAttributeMaxDynamicSharedMemorySize, SMEM_BYTES);
    cudaLaunchConfig_t cfg = {};
    cfg.gridDim = dim3(NCTA); cfg.blockDim = dim3(384); cfg.dynamicSmemBytes = SMEM_BYTES; cfg.stream = cudaStreamPerThread;
    cudaLaunchAttribute at[1];
    at[0].id = cudaLaunchAttributeClusterDimension; at[0].val.clusterDim.x = 2; at[0].val.clusterDim.y = 1; at[0].val.clusterDim.z = 1;
    cfg.attrs = at; cfg.numAttrs = 1;
    const Ptrs pt{(const __nv_bfloat16*)d_in[7], (Mail*)mail, (__nv_bfloat16*)hb};
    cudaLaunchKernelEx(&cfg, fused_block_kernel, pt, mp);
}
```

```cpp
#include <cuda_runtime.h>
#include <cuda_bf16.h>
#include <cuda.h>
#include <stdint.h>
#include <stddef.h>

#define LAG 3
#define LAGS 2
#define LAGW 3
#define LAGD 3
#define LAGQ 3
#define EARLY 1
#define NQ 6
#define NS 5
#define RC 224
#define RESTH 1000
#define NB0 2
#define EVB EV_PAR
#define EVS EV_WIN1
#define GW 4
#define GD 2
#define LSUB 1
#define QA 3
#define UNSAFE 0

namespace {

constexpr int S_ = 2048, D_ = 1024, F_ = 3584;
constexpr int NCTA = 132;
constexpr int NSLOT = 6;
constexpr uint32_t SLOT = 32768;
constexpr uint32_t OFF_STG = NSLOT * SLOT;
constexpr uint32_t OFF_BAR = OFF_STG + 32768;
constexpr uint32_t OFF_PAR = OFF_BAR + 384;
constexpr uint32_t OFF_TAB = OFF_PAR + 512;
constexpr uint32_t OFF_JUNK = 0u - 1024;
constexpr uint32_t SMEM_BYTES = 1024 + OFF_TAB + 1024;
constexpr int ST_Q = 33, ST_WO = ST_Q + NQ + NS, ST_GU = ST_WO + 16, ST_G1 = ST_GU + 33;
static_assert(ST_GU % NSLOT == 0, "");
constexpr uint32_t OFF_OWN = 5 * SLOT;
constexpr uint32_t sweep_order() {
    uint32_t v = 0, n = 0;
    for (uint32_t want = 0; want < NSLOT; ++want)
        for (int i = 0; i < NS; ++i) { const uint32_t t = ST_WO - NS + i, s = t % NSLOT; if (s == want) v |= (s | (t / NSLOT & 1) << 3) << (4 * n++); }
    return v;
}
constexpr uint32_t SWEEP = sweep_order();

constexpr int FL_DONE = 16 * 64, FL_LN2 = 16 * 64 + 1;

enum { L_WQKV, L_WKV, L_WQ, L_WO, L_WG, L_WU, L_WD, L_WMOD, L_H1, L_H1Q, L_X, L_O, L_H2, L_HB, L_COUNT };
struct Maps {
    CUtensorMap wm, h1s, os, h1r, orr, out, ld[L_COUNT];
};

struct Mail {
    uint32_t flags[16 * 64 + 32];
    uint2 mod[6 * D_ / 2];
    uint4 mod1[8 * 2048];
    uint4 st1[8 * S_ / 2];
    uint32_t par2[D_];
    uint4 halo[128 * 512];
};
struct Ptrs { const __nv_bfloat16* c; Mail* mail; __nv_bfloat16 *hb, *h1, *o; };

__device__ __align__(128) Mail g_mail;
__device__ __align__(128) __nv_bfloat16 g_h1[S_ * D_];
__device__ __align__(128) __nv_bfloat16 g_o[S_ * D_];
__device__ __align__(128) __nv_bfloat16 g_hb[S_ * F_];
#define TS(i) do {} while (0)
#define TW(i) do {} while (0)
#define TX(i) do {} while (0)
#define TR(w, n) do {} while (0)

__device__ __forceinline__ uint32_t smem_u32(const void* p) { return (uint32_t)__cvta_generic_to_shared(p); }
__device__ __forceinline__ void mbar_init(uint32_t bar, uint32_t cnt) { asm volatile("mbarrier.init.shared::cta.b64 [%0], %1;" :: "r"(bar), "r"(cnt) : "memory"); }
__device__ __forceinline__ void mbar_expect_tx(uint32_t bar, uint32_t bytes) { asm volatile("mbarrier.arrive.expect_tx.shared::cta.b64 _, [%0], %1;" :: "r"(bar), "r"(bytes) : "memory"); }
__device__ __forceinline__ void mbar_arrive(uint32_t bar) { asm volatile("mbarrier.arrive.shared::cta.b64 _, [%0];" :: "r"(bar) : "memory"); }
__device__ __forceinline__ void mbar_arrive_if0(uint32_t bar, uint32_t z) {
    asm volatile("{\n.reg .pred p;\nsetp.eq.u32 p, %1, 0;\n@p mbarrier.arrive.shared::cta.b64 _, [%0];\n}" :: "r"(bar), "r"(z) : "memory");
}
__device__ __forceinline__ void mbar_wait(uint32_t bar, uint32_t parity) {
    asm volatile("{\n.reg .pred p;\nW_LOOP:\nmbarrier.try_wait.parity.shared::cta.b64 p, [%0], %1;\n@!p bra W_LOOP;\n}" :: "r"(bar), "r"(parity) : "memory");
}
__device__ __forceinline__ void mbar_wait_b(uint32_t bar, uint32_t parity) {
    asm volatile("{\n.reg .pred p;\n.reg .u32 n;\nmov.u32 n, 0;\n"
        "W_LOOP:\nmbarrier.try_wait.parity.shared::cta.b64 p, [%0], %1;\n@p bra W_DONE;\n"
        "add.u32 n, n, 1;\nsetp.lt.u32 p, n, 0x400000;\n@p bra W_LOOP;\ntrap;\nW_DONE:\n}" :: "r"(bar), "r"(parity) : "memory");
}
__device__ __forceinline__ void tma_load(uint32_t dst, const CUtensorMap* m, int c0, int c1, uint32_t bar) {
    asm volatile("cp.async.bulk.tensor.2d.shared::cluster.global.mbarrier::complete_tx::bytes [%0], [%1, {%3, %4}], [%2];"
        :: "r"(dst), "l"(m), "r"(bar), "r"(c0), "r"(c1) : "memory");
}
__device__ __forceinline__ void tma_load4(uint32_t dst, const CUtensorMap* m, int c0, int c1, int c2, uint32_t bar) {
    asm volatile("cp.async.bulk.tensor.4d.shared::cluster.global.mbarrier::complete_tx::bytes [%0], [%1, {%3, %4, %5, %6}], [%2];"
        :: "r"(dst), "l"(m), "r"(bar), "r"(c0), "r"(c1), "r"(c2), "r"(0) : "memory");
}
__device__ __forceinline__ void tma_load5_mc(uint32_t dst, const CUtensorMap* m, int c0, int c1, int c2, int c3, int c4, uint32_t bar) {
    asm volatile("cp.async.bulk.tensor.5d.shared::cluster.global.mbarrier::complete_tx::bytes.multicast::cluster.L2::cache_hint [%0], [%1, {%3, %4, %5, %6, %7}], [%2], %8, %9;"
        :: "r"(dst), "l"(m), "r"(bar), "r"(c0), "r"(c1), "r"(c2), "r"(c3), "r"(c4), "h"((uint16_t)3), "l"(0x12F0000000000000ull) : "memory");
}
__device__ __forceinline__ void tma_store(const CUtensorMap* m, int c0, int c1, uint32_t src) {
    asm volatile("cp.async.bulk.tensor.2d.global.shared::cta.bulk_group [%0, {%2, %3}], [%1];" :: "l"(m), "r"(src), "r"(c0), "r"(c1) : "memory");
}
__device__ __forceinline__ void bulk_commit() { asm volatile("cp.async.bulk.commit_group;" ::: "memory"); }
__device__ __forceinline__ void bulk_wait_read() { asm volatile("cp.async.bulk.wait_group.read 0;" ::: "memory"); }
__device__ __forceinline__ void bulk_wait_all() { asm volatile("cp.async.bulk.wait_group 0;" ::: "memory"); }
__device__ __forceinline__ void fence_async_smem() { asm volatile("fence.proxy.async.shared::cta;" ::: "memory"); }
__device__ __forceinline__ void fence_async_global() { asm volatile("fence.proxy.async.global;" ::: "memory"); }
__device__ __forceinline__ void prefetch_map(const CUtensorMap* m) { asm volatile("prefetch.tensormap [%0];" :: "l"(m) : "memory"); }
__device__ __forceinline__ void wg_fence() { asm volatile("wgmma.fence.sync.aligned;" ::: "memory"); }
__device__ __forceinline__ void wg_commit() { asm volatile("wgmma.commit_group.sync.aligned;" ::: "memory"); }
template <int N> __device__ __forceinline__ void wg_wait() { asm volatile("wgmma.wait_group.sync.aligned %0;" :: "n"(N) : "memory"); }
__device__ __forceinline__ void bar_sync(int id, int n) { asm volatile("bar.sync %0, %1;" :: "r"(id), "r"(n) : "memory"); }
__device__ __forceinline__ void flag_add(uint32_t* f) { asm volatile("red.relaxed.gpu.global.add.u32 [%0], 1;" :: "l"(f) : "memory"); }
__device__ __forceinline__ uint32_t d16(uint32_t addr) { return (addr & 0x3FFFF) >> 4; }
__device__ __forceinline__ uint64_t mk_desc(uint32_t a16, uint32_t off, uint32_t lbo, uint32_t sbo, uint32_t swz) {
    const uint32_t lo = a16 + (off >> 4) + ((lbo >> 4) << 16), hi = (sbo >> 4) | (swz << 30);
    return ((uint64_t)hi << 32) | lo;
}
__device__ __forceinline__ uint32_t pack2(float lo, float hi) {
    uint32_t r; asm("cvt.rn.bf16x2.f32 %0, %1, %2;" : "=r"(r) : "f"(hi), "f"(lo)); return r;
}
__device__ __forceinline__ uint32_t hfma2_bf16(uint32_t a, uint32_t b, uint32_t c) {
    uint32_t r; asm("fma.rn.bf16x2 %0, %1, %2, %3;" : "=r"(r) : "r"(a), "r"(b), "r"(c)); return r;
}
__device__ __forceinline__ float bf_lo(uint32_t v) { return __uint_as_float(v << 16); }
__device__ __forceinline__ float bf_hi(uint32_t v) { return __uint_as_float(v & 0xFFFF0000u); }
__device__ __forceinline__ float bf_round(float x) { return __bfloat162float(__float2bfloat16_rn(x)); }
__device__ __forceinline__ void stsm4(uint32_t addr, uint32_t r0, uint32_t r1, uint32_t r2, uint32_t r3) {
    asm volatile("stmatrix.sync.aligned.m8n8.x4.shared.b16 [%0], {%1, %2, %3, %4};" :: "r"(addr), "r"(r0), "r"(r1), "r"(r2), "r"(r3) : "memory");
}
__device__ __forceinline__ void stsm4t(uint32_t addr, uint32_t r0, uint32_t r1, uint32_t r2, uint32_t r3) {
    asm volatile("stmatrix.sync.aligned.m8n8.x4.trans.shared.b16 [%0], {%1, %2, %3, %4};" :: "r"(addr), "r"(r0), "r"(r1), "r"(r2), "r"(r3) : "memory");
}
__device__ __forceinline__ void ldsm4(uint32_t addr, uint32_t& r0, uint32_t& r1, uint32_t& r2, uint32_t& r3) {
    asm volatile("ldmatrix.sync.aligned.m8n8.x4.shared.b16 {%0, %1, %2, %3}, [%4];" : "=r"(r0), "=r"(r1), "=r"(r2), "=r"(r3) : "r"(addr) : "memory");
}
__device__ __forceinline__ uint32_t movm(uint32_t a) { uint32_t r; asm volatile("movmatrix.sync.aligned.m8n8.trans.b16 %0, %1;" : "=r"(r) : "r"(a)); return r; }
__device__ __forceinline__ void mma16816(float (&c)[4], uint32_t a0, uint32_t a1, uint32_t a2, uint32_t a3, uint32_t b0, uint32_t b1) {
    asm("mma.sync.aligned.m16n8k16.row.col.f32.bf16.bf16.f32 {%0, %1, %2, %3}, {%4, %5, %6, %7}, {%8, %9}, {%0, %1, %2, %3};"
        : "+f"(c[0]), "+f"(c[1]), "+f"(c[2]), "+f"(c[3]) : "r"(a0), "r"(a1), "r"(a2), "r"(a3), "r"(b0), "r"(b1));
}
__device__ __forceinline__ float ex2(float x) { float r; asm("ex2.approx.ftz.f32 %0, %1;" : "=f"(r) : "f"(x)); return r; }
__device__ __forceinline__ float rcp(float x) { float r; asm("rcp.approx.ftz.f32 %0, %1;" : "=f"(r) : "f"(x)); return r; }
__device__ __forceinline__ float rsq(float x) { float r; asm("rsqrt.approx.ftz.f32 %0, %1;" : "=f"(r) : "f"(x)); return r; }
__device__ __forceinline__ float silu_(float x) { return __fdividef(x, 1.f + __expf(-x)); }
__device__ __forceinline__ void st_pkt(void* p, uint32_t a, uint32_t b) {
    asm volatile("{\n.reg .b64 t;\nmov.b64 t, {%1, %2};\nst.relaxed.gpu.global.b64 [%0], t;\n}" :: "l"(p), "r"(a), "r"(b) : "memory");
}
__device__ __forceinline__ uint2 ld_pkt(const void* p) {
    uint2 v; asm volatile("{\n.reg .b64 t;\nld.relaxed.gpu.global.b64 t, [%2];\nmov.b64 {%0, %1}, t;\n}" : "=r"(v.x), "=r"(v.y) : "l"(p) : "memory"); return v;
}
__device__ __forceinline__ void st_pkt16(void* p, uint32_t a, uint32_t b, uint32_t c, uint32_t d) {
    asm volatile("{\n.reg .b64 t, u;\n.reg .b128 w;\nmov.b64 t, {%1, %2};\nmov.b64 u, {%3, %4};\nmov.b128 w, {t, u};\nst.relaxed.gpu.global.b128 [%0], w;\n}"
        :: "l"(p), "r"(a), "r"(b), "r"(c), "r"(d) : "memory");
}
__device__ __forceinline__ uint4 ld_pkt16(const void* p) {
    uint4 v; asm volatile("{\n.reg .b64 t, u;\n.reg .b128 w;\nld.relaxed.gpu.global.b128 w, [%4];\nmov.b128 {t, u}, w;\nmov.b64 {%0, %1}, t;\nmov.b64 {%2, %3}, u;\n}"
        : "=r"(v.x), "=r"(v.y), "=r"(v.z), "=r"(v.w) : "l"(p) : "memory"); return v;
}
#define SPIN_GUARD(n) do { if (++(n) > (1u << 22)) asm volatile("trap;"); } while (0)
__device__ __forceinline__ uint4 lds128(uint32_t a) { uint4 v; asm volatile("ld.shared.v4.u32 {%0, %1, %2, %3}, [%4];" : "=r"(v.x), "=r"(v.y), "=r"(v.z), "=r"(v.w) : "r"(a) : "memory"); return v; }
__device__ __forceinline__ void sts128(uint32_t a, uint32_t x, uint32_t y, uint32_t z, uint32_t w) { asm volatile("st.shared.v4.u32 [%0], {%1, %2, %3, %4};" :: "r"(a), "r"(x), "r"(y), "r"(z), "r"(w) : "memory"); }
__device__ __forceinline__ uint2 lds64(uint32_t a) { uint2 v; asm volatile("ld.shared.v2.u32 {%0, %1}, [%2];" : "=r"(v.x), "=r"(v.y) : "r"(a) : "memory"); return v; }
__device__ __forceinline__ void sts64(uint32_t a, uint32_t x, uint32_t y) { asm volatile("st.shared.v2.u32 [%0], {%1, %2};" :: "r"(a), "r"(x), "r"(y) : "memory"); }
__device__ __forceinline__ uint32_t lds32(uint32_t a) { uint32_t v; asm volatile("ld.shared.u32 %0, [%1];" : "=r"(v) : "r"(a) : "memory"); return v; }
__device__ __forceinline__ void sts32(uint32_t a, uint32_t v) { asm volatile("st.shared.u32 [%0], %1;" :: "r"(a), "r"(v) : "memory"); }
__device__ __forceinline__ bool elect_one() {
    uint32_t p; asm volatile("{\n.reg .pred q;\nelect.sync _|q, 0xffffffff;\nselp.u32 %0, 1, 0, q;\n}" : "=r"(p)); return p;
}
__device__ __forceinline__ void cluster_arrive() { asm volatile("barrier.cluster.arrive.relaxed.aligned;" ::: "memory"); }
__device__ __forceinline__ void cluster_wait() { asm volatile("barrier.cluster.wait.aligned;" ::: "memory"); }

__device__ __forceinline__ void wgmma_n128_z(float (&d)[64], uint64_t da, uint64_t db) {
    asm volatile("{\n.reg .pred p;\nsetp.ne.b32 p, 0, 0;\n"
        "wgmma.mma_async.sync.aligned.m64n128k16.f32.bf16.bf16 {"
        "%0, %1, %2, %3, %4, %5, %6, %7, %8, %9, %10, %11, %12, %13, %14, %15, "
        "%16, %17, %18, %19, %20, %21, %22, %23, %24, %25, %26, %27, %28, %29, %30, %31, "
        "%32, %33, %34, %35, %36, %37, %38, %39, %40, %41, %42, %43, %44, %45, %46, %47, "
        "%48, %49, %50, %51, %52, %53, %54, %55, %56, %57, %58, %59, %60, %61, %62, %63"
        "}, %64, %65, p, 1, 1, 0, 1;\n}\n"
        : "=f"(d[0]), "=f"(d[1]), "=f"(d[2]), "=f"(d[3]), "=f"(d[4]), "=f"(d[5]), "=f"(d[6]), "=f"(d[7]),
          "=f"(d[8]), "=f"(d[9]), "=f"(d[10]), "=f"(d[11]), "=f"(d[12]), "=f"(d[13]), "=f"(d[14]), "=f"(d[15]),
          "=f"(d[16]), "=f"(d[17]), "=f"(d[18]), "=f"(d[19]), "=f"(d[20]), "=f"(d[21]), "=f"(d[22]), "=f"(d[23]),
          "=f"(d[24]), "=f"(d[25]), "=f"(d[26]), "=f"(d[27]), "=f"(d[28]), "=f"(d[29]), "=f"(d[30]), "=f"(d[31]),
          "=f"(d[32]), "=f"(d[33]), "=f"(d[34]), "=f"(d[35]), "=f"(d[36]), "=f"(d[37]), "=f"(d[38]), "=f"(d[39]),
          "=f"(d[40]), "=f"(d[41]), "=f"(d[42]), "=f"(d[43]), "=f"(d[44]), "=f"(d[45]), "=f"(d[46]), "=f"(d[47]),
          "=f"(d[48]), "=f"(d[49]), "=f"(d[50]), "=f"(d[51]), "=f"(d[52]), "=f"(d[53]), "=f"(d[54]), "=f"(d[55]),
          "=f"(d[56]), "=f"(d[57]), "=f"(d[58]), "=f"(d[59]), "=f"(d[60]), "=f"(d[61]), "=f"(d[62]), "=f"(d[63])
        : "l"(da), "l"(db));
}
__device__ __forceinline__ void wgmma_n128(float (&d)[64], uint64_t da, uint64_t db) {
    asm volatile("{\n.reg .pred p;\nsetp.eq.b32 p, 0, 0;\n"
        "wgmma.mma_async.sync.aligned.m64n128k16.f32.bf16.bf16 {"
        "%0, %1, %2, %3, %4, %5, %6, %7, %8, %9, %10, %11, %12, %13, %14, %15, "
        "%16, %17, %18, %19, %20, %21, %22, %23, %24, %25, %26, %27, %28, %29, %30, %31, "
        "%32, %33, %34, %35, %36, %37, %38, %39, %40, %41, %42, %43, %44, %45, %46, %47, "
        "%48, %49, %50, %51, %52, %53, %54, %55, %56, %57, %58, %59, %60, %61, %62, %63"
        "}, %64, %65, p, 1, 1, 0, 1;\n}\n"
        : "+f"(d[0]), "+f"(d[1]), "+f"(d[2]), "+f"(d[3]), "+f"(d[4]), "+f"(d[5]), "+f"(d[6]), "+f"(d[7]),
          "+f"(d[8]), "+f"(d[9]), "+f"(d[10]), "+f"(d[11]), "+f"(d[12]), "+f"(d[13]), "+f"(d[14]), "+f"(d[15]),
          "+f"(d[16]), "+f"(d[17]), "+f"(d[18]), "+f"(d[19]), "+f"(d[20]), "+f"(d[21]), "+f"(d[22]), "+f"(d[23]),
          "+f"(d[24]), "+f"(d[25]), "+f"(d[26]), "+f"(d[27]), "+f"(d[28]), "+f"(d[29]), "+f"(d[30]), "+f"(d[31]),
          "+f"(d[32]), "+f"(d[33]), "+f"(d[34]), "+f"(d[35]), "+f"(d[36]), "+f"(d[37]), "+f"(d[38]), "+f"(d[39]),
          "+f"(d[40]), "+f"(d[41]), "+f"(d[42]), "+f"(d[43]), "+f"(d[44]), "+f"(d[45]), "+f"(d[46]), "+f"(d[47]),
          "+f"(d[48]), "+f"(d[49]), "+f"(d[50]), "+f"(d[51]), "+f"(d[52]), "+f"(d[53]), "+f"(d[54]), "+f"(d[55]),
          "+f"(d[56]), "+f"(d[57]), "+f"(d[58]), "+f"(d[59]), "+f"(d[60]), "+f"(d[61]), "+f"(d[62]), "+f"(d[63])
        : "l"(da), "l"(db));
}
__device__ __forceinline__ void wgmma_n256_z(float (&d)[128], uint64_t da, uint64_t db) {
    asm volatile("{\n.reg .pred p;\nsetp.ne.b32 p, 0, 0;\n"
        "wgmma.mma_async.sync.aligned.m64n256k16.f32.bf16.bf16 {"
        "%0, %1, %2, %3, %4, %5, %6, %7, %8, %9, %10, %11, %12, %13, %14, %15, "
        "%16, %17, %18, %19, %20, %21, %22, %23, %24, %25, %26, %27, %28, %29, %30, %31, "
        "%32, %33, %34, %35, %36, %37, %38, %39, %40, %41, %42, %43, %44, %45, %46, %47, "
        "%48, %49, %50, %51, %52, %53, %54, %55, %56, %57, %58, %59, %60, %61, %62, %63, "
        "%64, %65, %66, %67, %68, %69, %70, %71, %72, %73, %74, %75, %76, %77, %78, %79, "
        "%80, %81, %82, %83, %84, %85, %86, %87, %88, %89, %90, %91, %92, %93, %94, %95, "
        "%96, %97, %98, %99, %100, %101, %102, %103, %104, %105, %106, %107, %108, %109, %110, %111, "
        "%112, %113, %114, %115, %116, %117, %118, %119, %120, %121, %122, %123, %124, %125, %126, %127"
        "}, %128, %129, p, 1, 1, 0, 1;\n}\n"
        : "=f"(d[0]), "=f"(d[1]), "=f"(d[2]), "=f"(d[3]), "=f"(d[4]), "=f"(d[5]), "=f"(d[6]), "=f"(d[7]),
          "=f"(d[8]), "=f"(d[9]), "=f"(d[10]), "=f"(d[11]), "=f"(d[12]), "=f"(d[13]), "=f"(d[14]), "=f"(d[15]),
          "=f"(d[16]), "=f"(d[17]), "=f"(d[18]), "=f"(d[19]), "=f"(d[20]), "=f"(d[21]), "=f"(d[22]), "=f"(d[23]),
          "=f"(d[24]), "=f"(d[25]), "=f"(d[26]), "=f"(d[27]), "=f"(d[28]), "=f"(d[29]), "=f"(d[30]), "=f"(d[31]),
          "=f"(d[32]), "=f"(d[33]), "=f"(d[34]), "=f"(d[35]), "=f"(d[36]), "=f"(d[37]), "=f"(d[38]), "=f"(d[39]),
          "=f"(d[40]), "=f"(d[41]), "=f"(d[42]), "=f"(d[43]), "=f"(d[44]), "=f"(d[45]), "=f"(d[46]), "=f"(d[47]),
          "=f"(d[48]), "=f"(d[49]), "=f"(d[50]), "=f"(d[51]), "=f"(d[52]), "=f"(d[53]), "=f"(d[54]), "=f"(d[55]),
          "=f"(d[56]), "=f"(d[57]), "=f"(d[58]), "=f"(d[59]), "=f"(d[60]), "=f"(d[61]), "=f"(d[62]), "=f"(d[63]),
          "=f"(d[64]), "=f"(d[65]), "=f"(d[66]), "=f"(d[67]), "=f"(d[68]), "=f"(d[69]), "=f"(d[70]), "=f"(d[71]),
          "=f"(d[72]), "=f"(d[73]), "=f"(d[74]), "=f"(d[75]), "=f"(d[76]), "=f"(d[77]), "=f"(d[78]), "=f"(d[79]),
          "=f"(d[80]), "=f"(d[81]), "=f"(d[82]), "=f"(d[83]), "=f"(d[84]), "=f"(d[85]), "=f"(d[86]), "=f"(d[87]),
          "=f"(d[88]), "=f"(d[89]), "=f"(d[90]), "=f"(d[91]), "=f"(d[92]), "=f"(d[93]), "=f"(d[94]), "=f"(d[95]),
          "=f"(d[96]), "=f"(d[97]), "=f"(d[98]), "=f"(d[99]), "=f"(d[100]), "=f"(d[101]), "=f"(d[102]), "=f"(d[103]),
          "=f"(d[104]), "=f"(d[105]), "=f"(d[106]), "=f"(d[107]), "=f"(d[108]), "=f"(d[109]), "=f"(d[110]), "=f"(d[111]),
          "=f"(d[112]), "=f"(d[113]), "=f"(d[114]), "=f"(d[115]), "=f"(d[116]), "=f"(d[117]), "=f"(d[118]), "=f"(d[119]),
          "=f"(d[120]), "=f"(d[121]), "=f"(d[122]), "=f"(d[123]), "=f"(d[124]), "=f"(d[125]), "=f"(d[126]), "=f"(d[127])
        : "l"(da), "l"(db));
}
__device__ __forceinline__ void wgmma_n256(float (&d)[128], uint64_t da, uint64_t db) {
    asm volatile("{\n.reg .pred p;\nsetp.eq.b32 p, 0, 0;\n"
        "wgmma.mma_async.sync.aligned.m64n256k16.f32.bf16.bf16 {"
        "%0, %1, %2, %3, %4, %5, %6, %7, %8, %9, %10, %11, %12, %13, %14, %15, "
        "%16, %17, %18, %19, %20, %21, %22, %23, %24, %25, %26, %27, %28, %29, %30, %31, "
        "%32, %33, %34, %35, %36, %37, %38, %39, %40, %41, %42, %43, %44, %45, %46, %47, "
        "%48, %49, %50, %51, %52, %53, %54, %55, %56, %57, %58, %59, %60, %61, %62, %63, "
        "%64, %65, %66, %67, %68, %69, %70, %71, %72, %73, %74, %75, %76, %77, %78, %79, "
        "%80, %81, %82, %83, %84, %85, %86, %87, %88, %89, %90, %91, %92, %93, %94, %95, "
        "%96, %97, %98, %99, %100, %101, %102, %103, %104, %105, %106, %107, %108, %109, %110, %111, "
        "%112, %113, %114, %115, %116, %117, %118, %119, %120, %121, %122, %123, %124, %125, %126, %127"
        "}, %128, %129, p, 1, 1, 0, 1;\n}\n"
        : "+f"(d[0]), "+f"(d[1]), "+f"(d[2]), "+f"(d[3]), "+f"(d[4]), "+f"(d[5]), "+f"(d[6]), "+f"(d[7]),
          "+f"(d[8]), "+f"(d[9]), "+f"(d[10]), "+f"(d[11]), "+f"(d[12]), "+f"(d[13]), "+f"(d[14]), "+f"(d[15]),
          "+f"(d[16]), "+f"(d[17]), "+f"(d[18]), "+f"(d[19]), "+f"(d[20]), "+f"(d[21]), "+f"(d[22]), "+f"(d[23]),
          "+f"(d[24]), "+f"(d[25]), "+f"(d[26]), "+f"(d[27]), "+f"(d[28]), "+f"(d[29]), "+f"(d[30]), "+f"(d[31]),
          "+f"(d[32]), "+f"(d[33]), "+f"(d[34]), "+f"(d[35]), "+f"(d[36]), "+f"(d[37]), "+f"(d[38]), "+f"(d[39]),
          "+f"(d[40]), "+f"(d[41]), "+f"(d[42]), "+f"(d[43]), "+f"(d[44]), "+f"(d[45]), "+f"(d[46]), "+f"(d[47]),
          "+f"(d[48]), "+f"(d[49]), "+f"(d[50]), "+f"(d[51]), "+f"(d[52]), "+f"(d[53]), "+f"(d[54]), "+f"(d[55]),
          "+f"(d[56]), "+f"(d[57]), "+f"(d[58]), "+f"(d[59]), "+f"(d[60]), "+f"(d[61]), "+f"(d[62]), "+f"(d[63]),
          "+f"(d[64]), "+f"(d[65]), "+f"(d[66]), "+f"(d[67]), "+f"(d[68]), "+f"(d[69]), "+f"(d[70]), "+f"(d[71]),
          "+f"(d[72]), "+f"(d[73]), "+f"(d[74]), "+f"(d[75]), "+f"(d[76]), "+f"(d[77]), "+f"(d[78]), "+f"(d[79]),
          "+f"(d[80]), "+f"(d[81]), "+f"(d[82]), "+f"(d[83]), "+f"(d[84]), "+f"(d[85]), "+f"(d[86]), "+f"(d[87]),
          "+f"(d[88]), "+f"(d[89]), "+f"(d[90]), "+f"(d[91]), "+f"(d[92]), "+f"(d[93]), "+f"(d[94]), "+f"(d[95]),
          "+f"(d[96]), "+f"(d[97]), "+f"(d[98]), "+f"(d[99]), "+f"(d[100]), "+f"(d[101]), "+f"(d[102]), "+f"(d[103]),
          "+f"(d[104]), "+f"(d[105]), "+f"(d[106]), "+f"(d[107]), "+f"(d[108]), "+f"(d[109]), "+f"(d[110]), "+f"(d[111]),
          "+f"(d[112]), "+f"(d[113]), "+f"(d[114]), "+f"(d[115]), "+f"(d[116]), "+f"(d[117]), "+f"(d[118]), "+f"(d[119]),
          "+f"(d[120]), "+f"(d[121]), "+f"(d[122]), "+f"(d[123]), "+f"(d[124]), "+f"(d[125]), "+f"(d[126]), "+f"(d[127])
        : "l"(da), "l"(db));
}
template <int O, int L>
__device__ __forceinline__ void wgmma_n64(float (&d)[L], uint64_t da, uint64_t db) {
    asm volatile("{\n.reg .pred p;\nsetp.eq.b32 p, 0, 0;\n"
        "wgmma.mma_async.sync.aligned.m64n64k16.f32.bf16.bf16 {%0, %1, %2, %3, %4, %5, %6, %7, %8, %9, %10, %11, %12, %13, %14, %15, %16, %17, %18, %19, %20, %21, %22, %23, %24, %25, %26, %27, %28, %29, %30, %31}, %32, %33, p, 1, 1, 0, 1;\n}\n"
        : "+f"(d[O + 0]), "+f"(d[O + 1]), "+f"(d[O + 2]), "+f"(d[O + 3]), "+f"(d[O + 4]), "+f"(d[O + 5]), "+f"(d[O + 6]), "+f"(d[O + 7]),
          "+f"(d[O + 8]), "+f"(d[O + 9]), "+f"(d[O + 10]), "+f"(d[O + 11]), "+f"(d[O + 12]), "+f"(d[O + 13]), "+f"(d[O + 14]), "+f"(d[O + 15]),
          "+f"(d[O + 16]), "+f"(d[O + 17]), "+f"(d[O + 18]), "+f"(d[O + 19]), "+f"(d[O + 20]), "+f"(d[O + 21]), "+f"(d[O + 22]), "+f"(d[O + 23]),
          "+f"(d[O + 24]), "+f"(d[O + 25]), "+f"(d[O + 26]), "+f"(d[O + 27]), "+f"(d[O + 28]), "+f"(d[O + 29]), "+f"(d[O + 30]), "+f"(d[O + 31])
        : "l"(da), "l"(db));
}

struct Idx {
    uint32_t lane, warp, w4, q4, g8, prow, pan;
    __device__ __forceinline__ Idx() {
        uint32_t t; asm volatile("mov.u32 %0, %%tid.x;" : "=r"(t));
        lane = t & 31; warp = t >> 5; w4 = warp & 3; q4 = lane & 3; g8 = lane >> 2;
        prow = w4 * 16 + ((lane >> 3) & 1) * 8 + (lane & 7);
        pan = prow * 128 + (((lane >> 4) ^ (lane & 7)) << 4);
    }
};
#define IDX() const Idx ix; const uint32_t lane = ix.lane, warp = ix.warp, w4 = ix.w4, q4 = ix.q4, g8 = ix.g8, prow = ix.prow, pan_addr = ix.pan; \
    (void)lane; (void)warp; (void)w4; (void)q4; (void)g8; (void)prow; (void)pan_addr;

struct Ring {
    uint32_t slot, par;
    __device__ __forceinline__ void next() { if (++slot == NSLOT) { slot = 0; par ^= 1; } }
};
__device__ __forceinline__ uint32_t BAR_FULL(uint32_t sb, uint32_t s) { return sb + OFF_BAR + 8 * s; }
__device__ __forceinline__ uint32_t BAR_EMPTY(uint32_t sb, uint32_t s) { return sb + OFF_BAR + 48 + 8 * s; }
__device__ __forceinline__ uint32_t BAR_SFULL(uint32_t sb, uint32_t i) { return sb + OFF_BAR + 96 + 8 * i; }
__device__ __forceinline__ uint32_t BAR_ONE(uint32_t sb, uint32_t i) { return sb + OFF_BAR + 160 + 8 * i; }
enum { EV_X, EV_WIN, EV_WIN1, EV_GA, EV_GB, EV_P2, EV_LAG0, EV_LAG1, EV_LAG2, EV_LAG3, EV_LAG4, EV_LAG5, EV_HB, EV_H, EV_H1, EV_H2, EV_SENT, EV_SEC, EV_BACK, EV_GO, EV_PAR, EV_COUNT };

enum { K_ABS, K_OWN, K_PANEL };
enum { F_WRAP = 1, F_TWICE = 2, F_SKIP = 4 };
constexpr uint32_t pre_ev(uint32_t ev) { return 160 + 8 * ev; }
constexpr uint32_t pre_sfull(uint32_t par) { return 96 + par; }
constexpr uint4 seg(uint32_t n, uint32_t kind, uint32_t a, uint32_t step, uint32_t q, uint32_t jump, uint32_t flags, uint32_t map, uint32_t kb, uint32_t pre = 0,
                    uint32_t blkj = 0, uint32_t blk = 0, uint32_t split = 0, uint32_t cnt = 0) {
    return uint4{n | (127 + q) / q << 8 | flags << 16 | map << 24, kind | a << 2 | step << 16 | jump / 64 << 24, kb | blkj << 8 | blk << 12 | split << 20, pre | cnt << 24};
}
constexpr int NSEG = 15;
__device__ const uint4 g_sched[3][NSEG] = {
    {seg(NB0, K_ABS, 0, 0, 1, 0, F_SKIP, L_WQKV, 0),
     seg(4 - NB0, K_OWN, NB0, 32, 32, 0, F_TWICE, L_WQKV, 24, pre_ev(EVB), 2, 0, 1),
     seg(28 - 2 * NQ, K_PANEL, 0, 32, 2, 64, F_WRAP, L_WQKV, 24, 0, 2, 0, 1), seg(2 * NQ, K_PANEL, 28 - 2 * NQ, 32, 2, 64, 0, L_WKV, 16, 0, 2, 0, 1),
     seg(NQ, K_PANEL, 28 - 2 * NQ, 64, 1, 64, 0, L_WQ, 16, 0, 2, 0, 3), seg(NS, K_PANEL, 28 - 2 * NQ - 2 * NS, 64, 1, 64, 0, L_WQ, 16, 0, 2, 0, 3),
     seg(2, K_OWN, 0, 64, 32, 0, 0, L_WO, 16, 0, 2, 0, 3), seg(14, K_PANEL, 0, 64, 1, 64, 0, L_WO, 16, 0, 2, 0, 3),
     seg(4, K_OWN, 0, 32, 32, 0, F_TWICE, L_WG, 24, 0, 7, 0, 2), seg(28, K_PANEL, 0, 32, 2, 64, F_WRAP, L_WG, 24, 0, 7, 0, 2),
     seg(32, K_ABS, 0, 32, 32, 0, 0, L_WG, 16, 0, 7, 3, 2), seg(32, K_ABS, 0, 32, 32, 0, 0, L_WG, 16, 0, 7, 5, 2),
     seg(24, K_ABS, 0, 64, 3, 256, 0, L_WD, 16, 0, 2, 0, 3), seg(16, K_ABS, 6, 64, 2, 320, 0, L_WD, 16, 0, 2, 0, 3), seg(16, K_ABS, 10, 64, 2, 320, 0, L_WD, 16, 0, 2, 0, 3)},
    {seg(4, K_ABS, 0, 0, 1, 0, F_SKIP, L_H1, 0),
     seg(28, K_PANEL, 0, 32, 2, 64, F_WRAP, L_H1, 8, pre_sfull(0), 0, 0, 0, 1),
     seg(NQ, K_PANEL, 28 - 2 * NQ, 64, 1, 64, 0, L_H1Q, 16), seg(NS, K_PANEL, 28 - 2 * NQ - 2 * NS, 64, 1, 64, 0, L_H1Q, 16),
     seg(2, K_OWN, 0, 64, 32, 0, 0, L_X, 16), seg(14, K_PANEL, 0, 64, 1, 64, 0, L_O, 16, pre_sfull(1), 0, 0, 0, 2),
     seg(4, K_ABS, 0, 0, 1, 0, F_SKIP, L_H2, 0), seg(28, K_PANEL, 0, 32, 2, 64, F_WRAP, L_H2, 8, pre_sfull(0), 0, 0, 0, 3),
     seg(32, K_ABS, 0, 32, 32, 0, 0, L_H2, 8, pre_ev(EV_SENT)), seg(32, K_ABS, 0, 32, 32, 0, 0, L_H2, 8),
     seg(24, K_ABS, 0, 64, 3, 256, 0, L_HB, 16, pre_ev(EV_H)), seg(16, K_ABS, 6, 64, 2, 320, 0, L_HB, 16, pre_ev(EV_H1)), seg(16, K_ABS, 10, 64, 2, 320, 0, L_HB, 16, pre_ev(EV_H2))},
    {seg(16, K_ABS, 0, 64, 32, 0, 0, L_WMOD, 32, pre_ev(EV_GO), 4, 32), seg(16, K_ABS, 0, 64, 32, 0, 0, L_WMOD, 32, 0, 4, 48),
     seg(16, K_ABS, 0, 64, 32, 0, 0, L_WMOD, 32, 0, 4, 64), seg(16, K_ABS, 0, 64, 32, 0, 0, L_WMOD, 32, 0, 4, 80)}};

struct Pipe {
    uint32_t sb, slot, par, tok, rel;
    __device__ __forceinline__ void arm() {
        uint32_t t, a; asm volatile("mov.u32 %0, %%tid.x;" : "=r"(t));
        asm("mapa.shared::cluster.u32 %0, %1, %2;" : "=r"(a) : "r"(BAR_EMPTY(sb, 0)), "r"((t >> 5) & 1));
        tok = __shfl_sync(0xffffffffu, (t & 95u) == 0 ? a : 0, t & 31);
    }
    __device__ __forceinline__ uint32_t stage() {
        mbar_wait(BAR_FULL(sb, slot), par);
        return d16(sb) + slot * (SLOT >> 4);
    }
    __device__ __forceinline__ void release() { if (rel) asm volatile("mbarrier.arrive.shared::cluster.b64 _, [%0];" :: "r"(rel) : "memory"); rel = 0; }
    __device__ __forceinline__ void issued() {
        wg_commit(); wg_wait<1>(); release();
        if (tok) rel = tok + 8 * slot;
        if (++slot == NSLOT) { slot = 0; par ^= 1; }
    }
    __device__ __forceinline__ void drain() { wg_wait<0>(); release(); }
    __device__ __forceinline__ void at(int stage) { slot = stage % NSLOT; par = (stage / NSLOT) & 1; }
};
enum { M_QKV, M_Q0KV, M_KV, M_GU3, M_GU2 };
template <int MODE, bool ZERO, bool OWN = false>
__device__ __forceinline__ void step32(float (&a256)[128], float (&a128)[64], Pipe& p, uint32_t wg, uint32_t own = 0) {
    constexpr uint32_t KS = MODE < M_KV ? 12288 : MODE == M_KV ? 8192 : 2048, LBO = MODE <= M_KV ? 2048 : 4096;
    constexpr uint32_t O256 = 8192 + (MODE < M_KV ? 4096 : 0), O128 = 8192 + (MODE < M_KV ? 0 : 16384);
    constexpr bool W128 = MODE == M_QKV || MODE == M_GU3;
    const uint32_t st = p.stage();
    wg_fence();
#pragma unroll
    for (int k = 0; k < 2; ++k) {
        const uint64_t da = OWN ? mk_desc(own, k * 32, 16, 1024, 1) : mk_desc(st + wg * 256, k * 32, 16, 512, 2);
        const uint64_t d0 = mk_desc(st, O256 + k * KS, LBO, 1024, 1), d1 = mk_desc(st, O128 + k * KS, LBO, 1024, 1);
        if (ZERO && k == 0) { wgmma_n256_z(a256, da, d0); if (W128) wgmma_n128_z(a128, da, d1); }
        else { wgmma_n256(a256, da, d0); if (W128) wgmma_n128(a128, da, d1); if (MODE == M_Q0KV) wgmma_n64<0>(a128, da, d1); }
    }
    p.issued();
}
struct Nop { __device__ __forceinline__ void operator()() const {} };
template <bool ZERO, class F = Nop>
__device__ __forceinline__ void step64(float (&acc)[64], Pipe& p, uint32_t wg, int own = -1, F landed = F()) {
    const uint32_t st = p.stage();
    landed();
    const uint32_t sa = own >= 0 ? d16(p.sb) + OFF_STG / 16 + wg * 512 + own * 1024 : st + wg * 512;
    wg_fence();
#pragma unroll
    for (int k = 0; k < 4; ++k) {
        const uint64_t da = mk_desc(sa, k * 32, 16, 1024, 1), db = mk_desc(st, 16384 + k * 2048, 8192, 1024, 1);
        if (ZERO && k == 0) wgmma_n128_z(acc, da, db); else wgmma_n128(acc, da, db);
    }
    p.issued();
}
__device__ __forceinline__ void rename(float (&d)[64], const float (&a)[64]) {
#pragma unroll
    for (int i = 0; i < 64; ++i) asm volatile("mov.b32 %0, %1;" : "=f"(d[i]) : "f"(a[i]));
}
template <int MODE, int ST>
__device__ __forceinline__ void run_own(float (&a256)[128], float (&a128)[64], Pipe& p, uint32_t wg) {
    const uint32_t a0 = d16(p.sb) + OFF_OWN / 16 + wg * 512;
    p.at(ST);
    step32<MODE, true, true>(a256, a128, p, wg, a0);
#pragma unroll 1
    for (int i = 1; i < 4; ++i) step32<MODE, false, true>(a256, a128, p, wg, a0 + (i >> 1) * 1024 + (i & 1) * 4);
    mbar_arrive_if0(BAR_FULL(p.sb, 5), threadIdx.x & 127);
    p.drain();
    p.at(ST + 4);
    step32<MODE, false>(a256, a128, p, wg);
    p.at(ST + 6);
}
template <int LG, class Step>
__device__ __forceinline__ void run(int n, uint32_t wg, uint32_t ev, Step step) {
    const int last = LG ? (wg ? EARLY : LG) : 0;
#pragma unroll 1
    for (int part = 0; ; ++part) {
#pragma unroll 1
        for (int i = part ? last : n - last; i > 0; --i) step();
        if (part || !LG) break;
        mbar_arrive_if0(ev, threadIdx.x ^ 128);
        if (wg == 0) mbar_wait(ev, 0);
    }
}

struct LnRow { float rs0, nm0, rs1, nm1; };
__device__ __forceinline__ void publish_stats(uint4* dst, float s0, float q0, float s1, float q1, uint32_t tag) {
    st_pkt16(dst, (__float_as_uint(s0) & ~3u) | tag, __float_as_uint(s1), __float_as_uint(q0), __float_as_uint(q1));
}
__device__ __forceinline__ LnRow merge_stats(const uint4* src, uint32_t tag) {
    uint4 a, b;
    do { a = ld_pkt16(src); b = ld_pkt16(src + S_ / 2); } while (!__all_sync(0xffffffffu, (a.x & b.x & tag) != 0));
    float v[4] = {__uint_as_float(a.x) + __uint_as_float(b.x), __uint_as_float(a.y) + __uint_as_float(b.y),
                  __uint_as_float(a.z) + __uint_as_float(b.z), __uint_as_float(a.w) + __uint_as_float(b.w)};
#pragma unroll
    for (int o = 1; o < 4; o <<= 1)
#pragma unroll
        for (int i = 0; i < 4; ++i) v[i] += __shfl_xor_sync(0xffffffffu, v[i], o);
    const float m0 = v[0] * (1.f / D_), m1 = v[1] * (1.f / D_);
    const float r0 = rsq(fmaxf(fmaf(-m0, m0, v[2] * (1.f / D_)), 0.f) + 1e-5f), r1 = rsq(fmaxf(fmaf(-m1, m1, v[3] * (1.f / D_)), 0.f) + 1e-5f);
    return LnRow{r0, -m0 * r0, r1, -m1 * r1};
}
__device__ __forceinline__ void ln_norm(uint32_t (&y)[32], const float (&x)[64], const LnRow& n) {
#pragma unroll
    for (int e = 0; e < 32; ++e) {
        const float rs = (e & 1) ? n.rs1 : n.rs0, nm = (e & 1) ? n.nm1 : n.nm0;
        y[e] = pack2(fmaf(x[2 * e], rs, nm), fmaf(x[2 * e + 1], rs, nm));
    }
}
__device__ __forceinline__ void ln_emit(const uint32_t (&y)[32], const uint4 (&p)[8], uint32_t sb, uint32_t wg, const Idx& ix) {
#pragma unroll
    for (int i = 0; i < 8; ++i) {
        uint32_t r[4];
#pragma unroll
        for (int e = 0; e < 4; ++e) r[e] = hfma2_bf16(y[4 * i + e], e < 2 ? p[i].z : p[i].w, e < 2 ? p[i].x : p[i].y);
        stsm4(sb + OFF_OWN + wg * 8192 + (i >> 2) * 16384 + (ix.pan ^ ((i & 3) << 5)), r[0], r[1], r[2], r[3]);
        if (i == 3) { __syncwarp(); if (ix.lane == 0) mbar_arrive(BAR_SFULL(sb, wg * 2)); }
    }
    fence_async_smem();
    __syncwarp();
    if (ix.lane == 0) mbar_arrive(BAR_SFULL(sb, wg * 2 + 1));
    bar_sync(1 + wg, 128);
}
template <int P>
__device__ __forceinline__ void load_panel(uint32_t (&r)[32], uint32_t p) {
    IDX();
#pragma unroll
    for (int i = 4 * P; i < 4 * P + 4; ++i) ldsm4(p + (pan_addr ^ ((i & 3) << 5)), r[4 * i], r[4 * i + 1], r[4 * i + 2], r[4 * i + 3]);
}
template <int E0 = 0, int E1 = 32>
__device__ __forceinline__ void widen(float (&x)[64], const uint32_t (&r)[32]) {
#pragma unroll
    for (int e = E0; e < E1; ++e) asm volatile("shl.b32 %0, %2, 16;\nand.b32 %1, %2, 0xFFFF0000;" : "=&f"(x[2 * e]), "=f"(x[2 * e + 1]) : "r"(r[e]));
}
template <int I0 = 0, int I1 = 8>
__device__ __forceinline__ void load_table(uint4 (&t)[8], uint32_t tab) {
#pragma unroll
    for (int i = I0; i < I1; ++i) t[i] = lds128(tab + i * 64 + (threadIdx.x & 3) * 16);
}
template <int STRIDE, class Step>
__device__ __forceinline__ void epilogue_operands(float (&x)[64], uint4 (&g)[8], uint32_t (&r)[32], uint32_t src, uint32_t tab, int first, Step step) {
#pragma unroll
    for (int i = 0; i < 64; ++i) asm volatile("" : "=f"(x[i]));
#pragma unroll
    for (int i = 0; i < 8; ++i) asm volatile("" : "=r"(g[i].x), "=r"(g[i].y), "=r"(g[i].z), "=r"(g[i].w));
#pragma unroll 1
    for (int it = first * STRIDE; it < 8 * STRIDE; ++it) {
        step([&] {
            if (it == 0) load_panel<0>(r, src);
            if (it == STRIDE) load_panel<1>(r, src + 16384);
            if (it == 6 * STRIDE) load_table<0, 4>(g, tab);
            if (it == 7 * STRIDE) load_table<4, 8>(g, tab);
        });
        if (it == 2 * STRIDE) widen<0, 8>(x, r);
        if (it == 3 * STRIDE) widen<8, 16>(x, r);
        if (it == 4 * STRIDE) widen<16, 24>(x, r);
        if (it == 5 * STRIDE) widen<24, 32>(x, r);
    }
}
__device__ __forceinline__ float gate_of(const uint4 (&t)[8], int e) {
    const uint4 v = t[e >> 3];
    return __uint_as_float((e & 4) ? ((e & 1) ? v.w : v.z) : ((e & 1) ? v.y : v.x));
}
__device__ __forceinline__ constexpr int glu_at(int i, int e) { return (i >> 2) * 64 + ((i >> 1) & 1) * 16 + (e >> 1) * 4 + (i & 1) * 2 + (e & 1); }
struct Raw { const float (&a)[64]; __device__ __forceinline__ float operator()(int e) const { return a[e]; } };
struct Packed {
    const uint32_t (&a)[64];
    __device__ __forceinline__ float operator()(int e) const {
        float v;
        if (e & 1) asm volatile("and.b32 %0, %1, 0xFFFF0000;" : "=f"(v) : "r"(a[e >> 1])); else asm volatile("shl.b32 %0, %1, 16;" : "=f"(v) : "r"(a[e >> 1]));
        return v;
    }
};
template <class A>
__device__ __forceinline__ void glu_tanh(float (&t)[8], A a, int i) {
#pragma unroll
    for (int e = 0; e < 8; ++e) asm volatile("tanh.approx.f32 %0, %1;" : "=f"(t[e]) : "f"(a(glu_at(i, e))));
}
template <class A>
__device__ __forceinline__ void glu_store(const float (&t)[8], A a, int i, __nv_bfloat16* dst) {
    uint32_t r[4];
#pragma unroll
    for (int c = 0; c < 4; ++c) {
        const float u0 = a(32 + glu_at(i, 2 * c)), u1 = a(33 + glu_at(i, 2 * c));
        r[c] = pack2(fmaf(t[2 * c], u0, u0), fmaf(t[2 * c + 1], u1, u1));
    }
    asm volatile("{\n.reg .pred p;\nsetp.eq.u32 p, %5, %6;\nG_LOOP:\nst.global.v4.u32 [%0], {%1, %2, %3, %4};\n@p bra G_LOOP;\n}"
        :: "l"(dst + (i & 1) * 8 * F_ + (i >> 1) * 32), "r"(r[0]), "r"(r[1]), "r"(r[2]), "r"(r[3]), "r"(blockIdx.y), "r"(1000 + i) : "memory");
}
__device__ __forceinline__ void glu_now(const float (&a)[64], __nv_bfloat16* dst) {
    float t[2][8];
#pragma unroll
    for (int i = 0; i <= 4; ++i) {
        if (i < 4) glu_tanh(t[i & 1], Raw{a}, i);
        if (i > 0) glu_store(t[(i - 1) & 1], Raw{a}, i - 1, dst);
    }
}
template <class Step>
__device__ __forceinline__ void glu_under(const uint32_t (&a)[64], __nv_bfloat16* dst, int n, Step step) {
#pragma unroll 1
    for (int it = -n; it < 16; ++it) {
        step();
        if (it >= 0 && !(it & 1)) {
#pragma unroll
            for (int i = 0; i < 8; ++i)
                if (it == 2 * i) { float t[8]; glu_tanh(t, Packed{a}, i); glu_store(t, Packed{a}, i, dst); }
        }
    }
}
__device__ __forceinline__ void pack_all(uint32_t (&d)[64], const float (&a)[128]) {
#pragma unroll
    for (int i = 0; i < 64; ++i) d[i] = pack2(a[2 * i], a[2 * i + 1]);
}

__global__ void __launch_bounds__(384, 1)
fused_block_kernel(const __grid_constant__ Ptrs pt, const __grid_constant__ Maps mp) {
    uint32_t* const g_flags = pt.mail->flags;
    uint2* const g_mod = pt.mail->mod;
    uint4* const g_st1 = pt.mail->st1;
    uint32_t* const g_par2 = pt.mail->par2;
    uint4* const g_halo = pt.mail->halo;
    const __nv_bfloat16* __restrict__ cvec = pt.c;
    if (threadIdx.x == 224) { prefetch_map(&mp.ld[L_X]); prefetch_map(&mp.wm); }
    extern __shared__ __align__(1024) uint8_t smem[];
    const uint32_t sb = smem_u32(smem) + 1024;
    const uint32_t tid = threadIdx.x, tw = tid & 127, lane = tid & 31;
    const uint32_t warp = __shfl_sync(0xffffffffu, tid >> 5, 0), wg = warp >> 2;
    uint32_t rank; asm("mov.u32 %0, %%cluster_ctarank;" : "=r"(rank));
    rank = __shfl_sync(0xffffffffu, rank, 0);
    uint32_t ep;
#define LOAD_EP() asm volatile("ld.relaxed.gpu.global.u32 %0, [%1];" : "=r"(ep) : "l"(&g_flags[FL_DONE]) : "memory")
    uint32_t smid; asm volatile("mov.u32 %0, %%smid;" : "=r"(smid));
    const int c = __shfl_sync(0xffffffffu, smid >> 1, 0);
    int grp, j;
    if (c < 32) { grp = c & 7; j = c >> 3; }
    else if (c < 60) { grp = 1 + (c - 32) % 7; j = 4 + (c - 32) / 7; }
    else if (c < 62) { grp = -1; j = (c - 60) * 2 + rank; }
    else { grp = 0; j = c - 58; }
    const bool aux = grp < 0;
    const int m = grp * 2 + rank;

    bool cluster_arrive_early = false;
    if (wg < 2) {
      LOAD_EP();
      cluster_arrive();
      if (aux) {
        if (wg == 0) {
            const uint4 cv = *(const uint4*)(cvec + tw * 8);
            sts128(sb + OFF_STG + (tw >> 3) * 1024 + (tw & 7) * 16, pack2(silu_(bf_lo(cv.x)), silu_(bf_hi(cv.x))), pack2(silu_(bf_lo(cv.y)), silu_(bf_hi(cv.y))),
                   pack2(silu_(bf_lo(cv.z)), silu_(bf_hi(cv.z))), pack2(silu_(bf_lo(cv.w)), silu_(bf_hi(cv.w))));
            fence_async_smem();
        }
        cluster_wait();
        ep = __shfl_sync(0xffffffffu, ep, 0) / NCTA + 1;
        if (wg == 0) {
            if (tw == 0) {
                uint32_t n = 0;
                while (!(ld_pkt16(pt.mail->mod1 + 256).x & (1 + (ep & 1)))) { SPIN_GUARD(n); __nanosleep(200); }
                mbar_arrive(BAR_ONE(sb, EV_GO));
            }
            bar_sync(1, 128);
            Ring r{0, 0};
#pragma unroll 1
            for (int p = 0; p < 4; ++p) {
                float acc[128];
#pragma unroll
                for (int i = 0; i < 128; ++i) acc[i] = 0.f;
                uint32_t prev = 0;
#pragma unroll 1
                for (int kc = 0; kc < 16; ++kc) {
                    mbar_wait(BAR_FULL(sb, r.slot), r.par);
                    wg_fence();
#pragma unroll
                    for (int k = 0; k < 4; ++k)
                        wgmma_n256(acc, mk_desc(d16(sb) + kc * 64, OFF_STG + k * 32, 16, 0, 1), mk_desc(d16(sb) + r.slot * (SLOT >> 4), k * 2048, 8192, 1024, 1));
                    wg_commit();
                    wg_wait<1>();
                    if (kc > 0 && tw == 0) mbar_arrive(BAR_EMPTY(sb, prev));
                    prev = r.slot;
                    r.next();
                }
                wg_wait<0>();
                if (tw == 0) mbar_arrive(BAR_EMPTY(sb, prev));
                if (tw < 4) {
#pragma unroll
                    for (int jn = 0; jn < 32; ++jn) sts32(sb + OFF_TAB + (jn * 4 + tw) * 4, pack2(acc[jn * 4], acc[jn * 4 + 1]));
                }
                bar_sync(1, 128);
                const int vec = 2 + p, blk = p * 4 + j;
                const uint32_t val = lds32(sb + OFF_TAB + tw * 4);
                if (vec == 2 || vec == 5) st_pkt(g_mod + (8 + blk) * 128 + tw, val, ep);
                else {
                    const float one = vec == 4 ? 1.f : 0.f;
                    g_par2[((blk & 3) * 16 + (tw >> 3)) * 16 + (tw & 3) * 4 + (vec - 3) * 2 + ((tw >> 2) & 1)] =
                        pack2(0.5f * bf_round(one + bf_lo(val)), 0.5f * bf_round(one + bf_hi(val)));
                }
                bar_sync(1, 128);
                if (tw == 0 && (vec == 3 || vec == 4)) asm volatile("red.release.gpu.global.add.u32 [%0], 1;" :: "l"(&g_flags[FL_LN2]) : "memory");
            }
        }
      } else {
        Pipe pp{sb, 0, 0, 0, 0};
        pp.arm();
        {
            IDX();
            uint4* const st1 = g_st1 + m * 64 + warp * 8 + g8;
            if (q4 == (g8 >> 1)) st_pkt16(st1 + j * (S_ / 2), 0, 0, 0, 0);
            cluster_wait();
            uint32_t xr[32];
            if (warp == 0) TX(0);
            mbar_wait(BAR_ONE(sb, EV_X), 0);
            if (warp == 0) TX(1);
            float sm[4] = {0.f, 0.f, 0.f, 0.f}, g0[4] = {0.f, 0.f, 0.f, 0.f}, g1[4] = {0.f, 0.f, 0.f, 0.f};
#pragma unroll
            for (int i = 0; i < 8; ++i) {
                ldsm4(sb + OFF_STG + wg * 8192 + (i >> 2) * 16384 + (pan_addr ^ ((i & 3) << 5)), xr[4 * i], xr[4 * i + 1], xr[4 * i + 2], xr[4 * i + 3]);
                mma16816(sm, xr[4 * i], xr[4 * i + 1], xr[4 * i + 2], xr[4 * i + 3], 0x3F803F80u, 0x3F803F80u);
                mma16816(g0, xr[4 * i], xr[4 * i + 1], xr[4 * i + 2], xr[4 * i + 3], xr[4 * i], xr[4 * i + 2]);
                mma16816(g1, xr[4 * i], xr[4 * i + 1], xr[4 * i + 2], xr[4 * i + 3], xr[4 * i + 1], xr[4 * i + 3]);
            }
            if (q4 == (g8 >> 1))
                publish_stats(st1 + j * (S_ / 2), sm[0], (g8 & 1) ? g0[1] : g0[0], sm[2], (g8 & 1) ? g1[3] : g1[2], 1);
            if (warp == 0) TX(2);
            float xf[64];
            widen(xf, xr);
            mbar_wait(BAR_ONE(sb, EVS), 0);
            const LnRow n1 = merge_stats(st1 + q4 * S_, 1);
            if (warp == 0) TX(5);
            ln_norm(xr, xf, n1);
            ep = __shfl_sync(0xffffffffu, ep, 0) / NCTA + 1;
            asm volatile("setmaxnreg.inc.sync.aligned.u32 %0;" :: "n"(RC));
            mbar_wait(BAR_ONE(sb, EV_PAR), 0);
            if (warp == 0) TX(6);
            uint4 par[8];
            load_table(par, sb + OFF_PAR);
            ln_emit(xr, par, sb, wg, ix);
            TW(0);
        }
        uint32_t xr[32];
        {
            float qa[64];
            uint32_t kl[16], kh[16], kp[16];
            uint32_t v0[32], v1[32];
            {
                float kv[128];
                float q1[64], q2[64];
                run_own<M_QKV, 0>(kv, q1, pp, wg);
                run<0>(27 - 2 * NS - 2 * NQ, wg, 0, [&] { step32<M_QKV, false>(kv, q1, pp, wg); });
                pp.drain();
                rename(q2, q1);
                run<0>(2 * NS, wg, 0, [&] { step32<M_Q0KV, false>(kv, q2, pp, wg); });
                run<LAGQ>(2 * NQ, wg, BAR_ONE(sb, EV_LAG0), [&] { step32<M_KV, false>(kv, q2, pp, wg); });
                pp.drain();
                rename(qa, q2);
                TW(1);
                IDX();
#pragma unroll
                for (int t = 0; t < 16; ++t) v1[(t >> 1) * 4 + 2 + (t & 1)] = movm(pack2(kv[66 + 4 * t], kv[67 + 4 * t]));
#pragma unroll
                for (int t = 0; t < 16; ++t) {
                    kl[t] = pack2(kv[4 * t], kv[4 * t + 1]); kh[t] = pack2(kv[4 * t + 2], kv[4 * t + 3]);
                    v1[(t >> 1) * 4 + (t & 1)] = pack2(kv[64 + 4 * t], kv[65 + 4 * t]);
                }
                if (w4 < 3) {
                    const uint32_t dst = sb + OFF_STG + wg * 8192 + (w4 >> 1) * 16384 + (w4 & 1) * 4096;
#pragma unroll
                    for (int i = 0; i < 4; ++i) sts128(dst + i * 512 + lane * 16, kh[4 * i], kh[4 * i + 1], kh[4 * i + 2], kh[4 * i + 3]);
#pragma unroll
                    for (int i = 0; i < 8; ++i) sts64(dst + 2048 + i * 256 + lane * 8, v1[4 * i + 2], v1[4 * i + 3]);
                } else if (m < 15) {
                    uint4* const dst = g_halo + (m * 8 + j) * 512 + wg * 256;
#pragma unroll
                    for (int i = 0; i < 4; ++i) { if (!kh[4 * i]) kh[4 * i] = 0x8000u; st_pkt16(dst + i * 32 + lane, kh[4 * i], kh[4 * i + 1], kh[4 * i + 2], kh[4 * i + 3]); }
#pragma unroll
                    for (int i = 0; i < 8; ++i) { if (!v1[4 * i + 2]) v1[4 * i + 2] = 0x8000u; st_pkt((uint2*)(dst + 128) + i * 32 + lane, v1[4 * i + 2], v1[4 * i + 3]); }
                }
                TW(2);
            }
            pp.at(ST_Q);
#pragma unroll 1
            for (int it = 0; it < QA; ++it) step64<false>(qa, pp, wg);
            IDX();
            uint4* const halo = g_halo + ((m - 1) * 8 + j) * 512 + wg * 256;
            auto fetch_halo = [&] {
#pragma unroll
                for (int i = 0; i < 4; ++i) {
                    const uint4 t = m > 0 ? ld_pkt16(halo + i * 32 + lane) : make_uint4(0, 0, 0, 0);
                    kp[4 * i] = t.x; kp[4 * i + 1] = t.y; kp[4 * i + 2] = t.z; kp[4 * i + 3] = t.w;
                }
#pragma unroll
                for (int i = 0; i < 8; ++i) {
                    const uint2 t = m > 0 ? ld_pkt((const uint2*)(halo + 128) + i * 32 + lane) : make_uint2(0, 0);
                    v0[4 * i] = t.x; v0[4 * i + 1] = t.y;
                }
            };
            bar_sync(1 + wg, 128);
#pragma unroll
            for (int t = 0; t < 16; ++t) v0[(t >> 1) * 4 + 2 + (t & 1)] = v1[(t >> 1) * 4 + (t & 1)] = movm(v1[(t >> 1) * 4 + (t & 1)]);
            if (w4 == 0) fetch_halo();
            else {
                const uint32_t src = sb + OFF_STG + wg * 8192 + ((w4 - 1) >> 1) * 16384 + ((w4 - 1) & 1) * 4096;
#pragma unroll
                for (int i = 0; i < 4; ++i) { const uint4 t = lds128(src + i * 512 + lane * 16); kp[4 * i] = t.x; kp[4 * i + 1] = t.y; kp[4 * i + 2] = t.z; kp[4 * i + 3] = t.w; }
#pragma unroll
                for (int i = 0; i < 8; ++i) { const uint2 t = lds64(src + 2048 + i * 256 + lane * 8); v0[4 * i] = t.x; v0[4 * i + 1] = t.y; }
            }
            TW(18);
            pp.at(ST_Q + QA);
#pragma unroll 1
            for (int it = QA; it < NQ; ++it) step64<false>(qa, pp, wg);
            bar_sync(1 + wg, 128);
            if (w4 == 0 && m > 0) {
                while (true) {
                    bool ok = true;
#pragma unroll
                    for (int i = 0; i < 8; ++i) ok = ok && v0[4 * i] != 0 && kp[4 * (i & 3)] != 0;
                    if (__all_sync(0xffffffffu, ok)) break;
                    fetch_halo();
                }
            }
            pp.drain();
            float qb[64];
            rename(qb, qa);
            TW(3);
            const bool lo0 = q4 * 2 > g8, lo1 = q4 * 2 + 1 > g8;
            const bool nopast = m == 0 && w4 == 0;
            const uint32_t lomask = (lo0 ? 0xFFFFu : 0u) | (lo1 ? 0xFFFF0000u : 0u);
            const float sl2 = 0.17677669529663687f * 1.4426950408889634f;
            const uint32_t oa = wg * 8192 + (w4 * 16 + (lane & 7)) * 128 + (((lane >> 3) ^ (lane & 7)) << 4);
#pragma unroll
            for (int hp = 0; hp < 2; ++hp) {
                if (hp) {
                    bar_sync(3, 256);
#pragma unroll 1
                    for (int it = 0; it < NS; ++it) {
                        pp.slot = (SWEEP >> (4 * it)) & 7; pp.par = (SWEEP >> (4 * it + 3)) & 1;
                        const uint32_t st = pp.stage();
                        wg_fence();
#pragma unroll
                        for (int k = 0; k < 4; ++k) wgmma_n64<32>(qb, mk_desc(st + wg * 512, k * 32, 16, 1024, 1), mk_desc(st, 24576 + k * 2048, 8192, 1024, 1));
                        pp.issued();
                    }
                    mbar_wait(BAR_FULL(sb, ST_WO % NSLOT), (ST_WO / NSLOT) & 1);
                    pp.drain();
                    load_panel<0>(xr, sb + ST_WO % NSLOT * SLOT + wg * 8192);
                    TW(4);
                }
                float e0[4], e1[4], mx[4], sum[4];
#pragma unroll
                for (int hh = 0; hh < 2; ++hh) {
                    const int h = 2 * hp + hh;
                    uint32_t qf[8];
                    float s[3][4];
#pragma unroll
                    for (int i = 0; i < 8; ++i) qf[i] = pack2(qb[16 * h + 2 * i], qb[16 * h + 2 * i + 1]);
#pragma unroll
                    for (int nt = 0; nt < 3; ++nt) {
                        const uint32_t (&kk)[16] = nt == 0 ? kp : nt == 1 ? kl : kh;
                        s[nt][0] = s[nt][1] = s[nt][2] = s[nt][3] = 0.f;
                        mma16816(s[nt], qf[0], qf[1], qf[2], qf[3], kk[4 * h], kk[4 * h + 1]);
                        mma16816(s[nt], qf[4], qf[5], qf[6], qf[7], kk[4 * h + 2], kk[4 * h + 3]);
                    }
#pragma unroll
                    for (int hf = 0; hf < 2; ++hf) {
                        e0[2 * hh + hf] = lo0 ? ((hf == 0 && nopast) ? -INFINITY : s[hf][hf * 2]) : s[hf + 1][hf * 2];
                        e1[2 * hh + hf] = lo1 ? ((hf == 0 && nopast) ? -INFINITY : s[hf][hf * 2 + 1]) : s[hf + 1][hf * 2 + 1];
                        mx[2 * hh + hf] = fmaxf(e0[2 * hh + hf], e1[2 * hh + hf]);
                    }
                }
#pragma unroll
                for (int o = 1; o < 4; o <<= 1)
#pragma unroll
                    for (int u = 0; u < 4; ++u) mx[u] = fmaxf(mx[u], __shfl_xor_sync(0xffffffffu, mx[u], o));
#pragma unroll
                for (int u = 0; u < 4; ++u) {
                    const float c = -mx[u] * sl2;
                    e0[u] = ex2(fmaf(e0[u], sl2, c)); e1[u] = ex2(fmaf(e1[u], sl2, c));
                    sum[u] = e0[u] + e1[u];
                }
#pragma unroll
                for (int o = 1; o < 4; o <<= 1)
#pragma unroll
                    for (int u = 0; u < 4; ++u) sum[u] += __shfl_xor_sync(0xffffffffu, sum[u], o);
#pragma unroll
                for (int u = 0; u < 4; ++u) {
                    const int h = 2 * hp + (u >> 1), hf = u & 1;
                    const uint32_t (&vv)[32] = hf ? v1 : v0;
                    const float iv = rcp(sum[u]);
                    const uint32_t pr = pack2(e0[u] * iv, e1[u] * iv);
                    float o[2][4];
#pragma unroll
                    for (int t = 0; t < 2; ++t) {
                        o[t][0] = o[t][1] = o[t][2] = o[t][3] = 0.f;
                        mma16816(o[t], vv[8 * h + 4 * t], vv[8 * h + 4 * t + 1], vv[8 * h + 4 * t + 2], vv[8 * h + 4 * t + 3], pr & lomask, pr & ~lomask);
                    }
                    stsm4t(sb + OFF_STG + hp * 16384 + (oa ^ ((h & 1) << 6)) + hf * 1024, pack2(o[0][0], o[0][1]), pack2(o[0][2], o[0][3]), pack2(o[1][0], o[1][1]), pack2(o[1][2], o[1][3]));
                }
                __syncwarp();
                if (lane == 0) mbar_arrive(BAR_SFULL(sb, wg * 2 + hp));
                if (!hp) TW(19);
            }
            TW(5);
        }
        {
            float acc[64], xf[64];
            uint4 gt[8], par[8];
            fence_async_smem();
            bar_sync(3, 256);
            pp.at(ST_WO);
            mbar_wait(BAR_FULL(sb, (ST_WO + 1) % NSLOT), ((ST_WO + 1) / NSLOT) & 1);
            step64<true>(acc, pp, wg, 0, [&] { load_panel<1>(xr, sb + (ST_WO + 1) % NSLOT * SLOT + wg * 8192); });
            step64<false>(acc, pp, wg, 1);
            fence_async_smem();
            bar_sync(1 + wg, 128);
            mbar_wait(BAR_ONE(sb, EV_GA), 0);
            pp.drain();
            uint4* const pub = g_st1 + __shfl_sync(0xffffffffu, j * (S_ / 2) + m * 64 + (tid >> 2), lane);
            pp.at(ST_WO + 2);
            epilogue_operands<1>(xf, gt, xr, 0, sb + OFF_TAB, 2, [&](auto f) { step64<false>(acc, pp, wg, -1, f); });
            run<LAGW>(8, wg, BAR_ONE(sb, EV_LAG4), [&] { step64<false>(acc, pp, wg); });
            pp.drain();
            TW(6);
            float su[4] = {0.f, 0.f, 0.f, 0.f}, sq[4] = {0.f, 0.f, 0.f, 0.f};
#pragma unroll
            for (int e = 0; e < 64; ++e) {
                xf[e] = fmaf(gate_of(gt, e), acc[e], xf[e]);
                su[e & 3] += xf[e]; sq[e & 3] = fmaf(xf[e], xf[e], sq[e & 3]);
            }
            {
                float v[4] = {su[0] + su[1], sq[0] + sq[1], su[2] + su[3], sq[2] + sq[3]};
#pragma unroll
                for (int o = 1; o < 4; o <<= 1)
#pragma unroll
                    for (int i = 0; i < 4; ++i) v[i] += __shfl_xor_sync(0xffffffffu, v[i], o);
                if ((tid & 3) == 0) publish_stats(pub, v[0], v[1], v[2], v[3], 2);
            }
            IDX();
            mbar_wait(BAR_ONE(sb, EV_P2), 0);
            TW(7);
#pragma unroll
            for (int i = 0; i < 8; ++i)
                stsm4(sb + OFF_STG + wg * 8192 + (i >> 2) * 16384 + (pan_addr ^ ((i & 3) << 5)), pack2(xf[8 * i], xf[8 * i + 1]), pack2(xf[8 * i + 2], xf[8 * i + 3]),
                      pack2(xf[8 * i + 4], xf[8 * i + 5]), pack2(xf[8 * i + 6], xf[8 * i + 7]));
            load_table(par, sb + OFF_PAR);
            mbar_wait(BAR_EMPTY(sb, (ST_GU - 1) % NSLOT), ((ST_GU - 1) / NSLOT) & 1);
            if (warp == 0) TX(8);
            const LnRow n2 = merge_stats(pub + ((int)q4 * 2 - j) * (S_ / 2), 2);
            TW(8);
            ln_norm(xr, xf, n2);
            ln_emit(xr, par, sb, wg, ix);
            TW(9);
        }
        {
            auto h_at = [&](int col) { IDX(); return pt.hb + (m * 128 + warp * 16 + g8) * F_ + j * 448 + col + q4 * 8; };
            uint32_t gu[64];
            {
                float a256[128], a128[64];
                run_own<M_GU3, ST_GU>(a256, a128, pp, wg);
                run<LAG>(27, wg, BAR_ONE(sb, EV_LAG1), [&] { step32<M_GU3, false>(a256, a128, pp, wg); });
                __nv_bfloat16* const dst = h_at(128);
                pp.drain();
                TW(10);
                glu_now(a128, dst);
                pack_all(gu, a256);
                TW(11);
            }
#pragma unroll 1
            for (int p = 0; p < 2; ++p) {
                float b256[128], none[64];
                pp.at(p ? ST_G1 + 32 : ST_G1);
                step32<M_GU2, true>(b256, none, pp, wg);
                glu_under(gu, h_at(p * 192), GW + wg, [&] { step32<M_GU2, false>(b256, none, pp, wg); });
                mbar_arrive_if0(BAR_ONE(sb, EV_HB), lane);
                run<LAGS>(15 - GW - wg, wg, BAR_ONE(sb, EV_LAG2 + p), [&] { step32<M_GU2, false>(b256, none, pp, wg); });
                pp.drain();
                TW(12 + 2 * p);
                pack_all(gu, b256);
                TW(13 + 2 * p);
            }
            float acc[64], xf[64];
            uint4 gt[8];
            pp.at(ST_G1 + 64);
            step64<true>(acc, pp, wg);
            glu_under(gu, h_at(320), GD + wg, [&] { step64<false>(acc, pp, wg); });
            mbar_arrive_if0(BAR_ONE(sb, EV_HB), lane);
            uint32_t x1[32];
#pragma unroll
            for (int i = 0; i < 32; ++i) asm volatile("" : "=r"(x1[i]));
            mbar_wait(BAR_ONE(sb, EV_GB), 0);
            epilogue_operands<2>(xf, gt, x1, sb + OFF_STG + wg * 8192, sb + OFF_TAB + 512, 0, [&](auto f) { step64<false>(acc, pp, wg, -1, f); });
            run<LAGD>(23 - GD - wg, wg, BAR_ONE(sb, EV_LAG5), [&] { step64<false>(acc, pp, wg); });
            cluster_arrive();
            const uint32_t warp_u = warp;
            IDX();
            wg_wait<0>();
            TW(16);
#pragma unroll
            for (int p = 0; p < 2; ++p) {
#pragma unroll
                for (int i = 4 * p; i < 4 * p + 4; ++i) {
                    uint32_t r[4];
#pragma unroll
                    for (int e = 0; e < 4; ++e)
                        r[e] = pack2(fmaf(gate_of(gt, 8 * i + 2 * e), acc[8 * i + 2 * e], xf[8 * i + 2 * e]), fmaf(gate_of(gt, 8 * i + 2 * e + 1), acc[8 * i + 2 * e + 1], xf[8 * i + 2 * e + 1]));
                    stsm4(sb + OFF_STG + wg * 8192 + p * 16384 + (pan_addr ^ ((i & 3) << 5)), r[0], r[1], r[2], r[3]);
                }
                fence_async_smem();
                __syncwarp();
                if (elect_one())
                    tma_store(&mp.out, wg * D_ + j * 128 + p * 64, m * 64 + (warp_u & 3) * 16, sb + OFF_STG + wg * 8192 + p * 16384 + (warp_u & 3) * 2048);
            }
            bulk_commit();
            bulk_wait_read();
            mbar_arrive_if0(BAR_SFULL(sb, wg * 2), lane);
            TW(17);
        }
      }
    } else {
        if (elect_one()) {
            if (warp == 8) {
                mbar_init(BAR_ONE(sb, EV_X), 1);
                if (!aux) {
                    mbar_expect_tx(BAR_ONE(sb, EV_X), 32768);
#pragma unroll
                    for (int i = 0; i < 2; ++i) tma_load4(sb + OFF_STG + i * 16384, &mp.ld[L_X], j * 128 + i * 64, m * 64, 0, BAR_ONE(sb, EV_X));
                }
#pragma unroll
                for (int i = 0; i < 2; ++i) {
                    mbar_init(BAR_ONE(sb, EV_WIN + i), 1);
                    if (!aux) {
                        mbar_expect_tx(BAR_ONE(sb, EV_WIN + i), 16384);
                        tma_load(sb + OFF_OWN + i * 16384, &mp.wm, (m * 2 + (j >> 2)) * 64, (j & 3) * 256 + i * 128, BAR_ONE(sb, EV_WIN + i));
                    }
                }
                prefetch_map(&mp.ld[aux ? L_WMOD : L_WQKV]);
            } else if (warp < 11) {
#pragma unroll
                for (int i = 0; i < 3; ++i) mbar_init(BAR_FULL(sb, (warp - 9) * 3 + i), aux ? 1 : 2);
#pragma unroll
                for (int i = 0; i < 2; ++i) mbar_init(BAR_SFULL(sb, (warp - 9) * 2 + i), 4);
#pragma unroll
                for (int i = 0; i < 3; ++i) mbar_init(BAR_EMPTY(sb, (warp - 9) * 3 + i), aux ? 1 : 4);
            } else {
#pragma unroll
                for (int i = EV_GA; i < EV_COUNT; ++i) mbar_init(BAR_ONE(sb, i), i == EV_HB ? 8 : i == EV_P2 ? 2 : 1);
            }
            asm volatile("fence.mbarrier_init.release.cluster;" ::: "memory");
        }
        __syncwarp();
        LOAD_EP();
        uint4 sg = make_uint4(0, 0, 0, 0);
        const uint4 cv = *(const uint4*)(cvec + (j & 3) * 256 + lane * 8);
        uint4* const modp = pt.mail->mod1 + (lane >> 2) * 2048 + (j & 3) * 512 + ((m * 2 + (j >> 2)) * 4 + (warp & 3)) * 4 + (lane & 3);
        if (!aux) st_pkt16(modp, 0, 0, 0, 0);
        if (lane < NSEG) sg = g_sched[aux ? 2 : warp == 11][lane];
        cluster_arrive();
        cluster_wait();
        const bool el = elect_one();
        const int kown = j * 128;
        if (!aux) {
            if (warp == 8 && el) {
#pragma unroll
                for (int i = 0; i < NB0; ++i) {
                    mbar_arrive(BAR_FULL(sb, i));
                    mbar_expect_tx(BAR_FULL(sb, i), 24576);
                    tma_load5_mc(sb + i * SLOT + 8192 + rank * 12288, &mp.ld[L_WQKV], 0, kown + i * 32 + rank * 16, 2 * j, 0, 0, BAR_FULL(sb, i));
                }
            }
            const uint32_t s0 = pack2(silu_(bf_lo(cv.x)), silu_(bf_hi(cv.x))), s1 = pack2(silu_(bf_lo(cv.y)), silu_(bf_hi(cv.y))),
                           s2 = pack2(silu_(bf_lo(cv.z)), silu_(bf_hi(cv.z))), s3 = pack2(silu_(bf_lo(cv.w)), silu_(bf_hi(cv.w)));
#pragma unroll
            for (int i = 0; i < 2; ++i) { const uint32_t row = (warp & 3) + 4 * i; sts128(sb + 4 * SLOT + (lane >> 3) * 1024 + row * 128 + (((lane & 7) ^ row) << 4), s0, s1, s2, s3); }
            fence_async_smem();
            bar_sync(4, 128);
            ep = __shfl_sync(0xffffffffu, ep, 0) / NCTA + 1;
            float acc[32];
#pragma unroll
            for (int i = 0; i < 32; ++i) acc[i] = 0.f;
#pragma unroll 1
            for (int h = 0; h < 2; ++h) {
                mbar_wait(BAR_ONE(sb, EV_WIN + h), 0);
                if (warp == 11) TX(3);
                wg_fence();
#pragma unroll
                for (int k = 0; k < 8; ++k)
                    wgmma_n64<0>(acc, mk_desc(d16(sb) + h * 128, 4 * SLOT + (k >> 2) * 1024 + (k & 3) * 32, 16, 0, 1), mk_desc(d16(sb) + h * 1024, OFF_OWN + k * 2048, 8192, 1024, 1));
                wg_commit();
            }
            wg_wait<0>();
            const uint32_t i = warp & 3;
            auto pick = [&](int e) { return __float_as_uint(i & 2 ? (i & 1 ? acc[24 + e] : acc[16 + e]) : (i & 1 ? acc[8 + e] : acc[e])); };
            st_pkt16(modp, (pick(0) & ~3u) | (1 + (ep & 1)), pick(1), pick(4), pick(5));
            if (warp == 11) TX(4);
        } else ep = __shfl_sync(0xffffffffu, ep, 0) / NCTA + 1;
        asm volatile("setmaxnreg.dec.sync.aligned.u32 %0;" :: "n"(504 - 2 * RC));

        if (warp == 8 || (warp == 11 && !aux)) {
            const bool act = warp == 11;
            if (act) {
                const uint4* pk = pt.mail->mod1 + grp * 2048 + j * 32 + lane;
                uint4 a[8];
                while (true) {
                    uint32_t t = 1 + (ep & 1);
#pragma unroll
                    for (int i = 0; i < 8; ++i) { a[i] = ld_pkt16(pk + i * 256); t &= a[i].x; }
                    if (__all_sync(0xffffffffu, t != 0)) break;
                }
                uint32_t r[4];
#pragma unroll
                for (int v = 0; v < 2; ++v) {
                    auto sum = [&](uint32_t uint4::*f) { return bf_round((__uint_as_float(a[v].*f) + __uint_as_float(a[2 + v].*f)) + (__uint_as_float(a[4 + v].*f) + __uint_as_float(a[6 + v].*f))) + v; };
                    r[2 * v] = pack2(sum(&uint4::x), sum(&uint4::y)); r[2 * v + 1] = pack2(sum(&uint4::z), sum(&uint4::w));
                }
                sts128(sb + OFF_PAR + lane * 16, r[0], r[1], r[2], r[3]);
                __syncwarp();
                if (el) mbar_arrive(BAR_ONE(sb, EV_PAR));
                if (warp == 11) TX(7);
            }
            {
                const uint32_t split = sg.z >> 20, bytes = (sg.z & 63) << 10;
                const uint32_t dst = split ? (split == 3 ? 16384 : 8192) + rank * (split == 2 ? 4096 : bytes >> 1) : 0;
                const uint32_t blk = ((sg.z >> 8) & 15) * j + ((sg.z >> 12) & 255) + (split == 3 ? rank : 0);
                if (split == 2) sg.x += rank << 24;
                if (split == 1) sg.y |= rank << 12;
                sg.z = dst | blk << 16 | (sg.z & 63) << 24;
            }
            Ring r{0, 1};
#pragma unroll 1
            for (int s = 0; ; ++s) {
                const uint32_t x = __shfl_sync(0xffffffffu, sg.x, s), y = __shfl_sync(0xffffffffu, sg.y, s), z = __shfl_sync(0xffffffffu, sg.z, s), w = __shfl_sync(0xffffffffu, sg.w, s);
                const uint32_t nx = __shfl_sync(0xffffffffu, sg.x, s + 1);
                if (!x) break;
                if (el) prefetch_map(&mp.ld[nx >> 24]);
                const CUtensorMap* const tm = &mp.ld[x >> 24];
                const uint32_t n = x & 255, blk = (z >> 16) & 255, bytes = (z >> 24) << 10, cnt = w >> 24, base = sb + (z & 0xFFFF);
                if (x & (F_SKIP << 16)) {
                    r.slot += n;
                    if (r.slot >= NSLOT) { r.slot -= NSLOT; r.par ^= 1; }
                    continue;
                }
                uint32_t kl;
                {
                    const uint32_t a = (y >> 2) & 63, step = (y >> 16) & 255, ch = a + lane * (step >> 5), u = ch >> 1, q = u < 7 ? u : u - 7;
                    kl = (y & 3) == K_PANEL ? (q + (q >= j)) * 128 + (u < 7 ? 0 : 64) + (ch & 1) * 32
                                            : ch * 32 + ((lane * ((x >> 8) & 255)) >> 7) * (y >> 24) * 64 + ((y & 3) == K_OWN ? kown : 0);
                    kl += (y >> 8) & 16;
                }
                uint32_t wrap = NSLOT - ((x >> 16) & F_WRAP);
                auto acquire = [&](uint32_t& st, uint32_t& fb) {
                    mbar_wait(BAR_EMPTY(sb, r.slot), r.par);
                    st = base + r.slot * SLOT; fb = BAR_FULL(sb, r.slot);
                    if (++r.slot == wrap) { r.slot = 0; r.par ^= 1; }
                    wrap = NSLOT;
                };
                uint32_t st, fb;
                if (w & 0xFFFF) { mbar_wait(sb + OFF_BAR + (w & 0xFFF8), w & 1); fence_async_global(); }
                if (act | aux) {
                    const uint32_t* const fl = g_flags + m * 64 + cnt * 16 + ((kl >> 6) & 15);
                    const int row = (x >> 24) == L_X ? m * 64 : m * 128;
                    const uint32_t trig = (x & (F_WRAP << 16)) ? 5 : 255;
                    uint32_t ready = cnt ? 0 : ~0u;
#pragma unroll 1
                    for (uint32_t i = 0; i < n; ++i) {
                        const uint32_t k = __shfl_sync(0xffffffffu, kl, i);
                        while (!((ready >> i) & 1)) {
                            uint32_t v; asm volatile("ld.relaxed.gpu.global.u32 %0, [%1];" : "=r"(v) : "l"(fl) : "memory");
                            ready = __ballot_sync(0xffffffffu, v == ep);
                            fence_async_global();
                        }
                        acquire(st, fb);
                        if (el) { mbar_expect_tx(fb, bytes); tma_load4(st, tm, aux ? 0 : k, aux ? k : row, aux ? blk : 0, fb); }
                        if (el && i == trig) mbar_arrive(BAR_ONE(sb, EV_SEC));
                    }
                } else {
                    const bool twice = el && (x & (F_TWICE << 16)), wd = (x >> 24) == L_WD;
                    const uint32_t more = (x >> 25) == L_WG / 2 ? (bytes >> 13) - 1 : 0;
#pragma unroll 1
                    for (uint32_t i = 0; i < n; ++i) {
                        const uint32_t k = __shfl_sync(0xffffffffu, kl, i);
                        acquire(st, fb);
                        if (twice) mbar_arrive(fb);
                        if (el) { mbar_expect_tx(fb, bytes); tma_load5_mc(st, tm, wd ? blk * 64 : 0, wd ? 0 : k, wd ? 0 : blk, (x >> 24) == L_WKV, wd ? k >> 5 : 0, fb); }
                        if (more && el) tma_load5_mc(st + 8192, tm, 0, k, blk + 1, 0, 0, fb);
                        if (more > 1 && el) tma_load5_mc(st + 16384, tm, 0, k, blk + 2, 0, 0, fb);
                    }
                }
            }
        } else if (!aux) {
            const uint32_t w = warp - 9;
            uint32_t par = 0;
            auto send = [&](const CUtensorMap* tm, uint32_t src, bool ring, int t) {
#pragma unroll 1
                for (uint32_t p = 0; p < 2; ++p) {
                    if (p && ring) mbar_wait_b(BAR_ONE(sb, EV_SEC), t >> 1);
#pragma unroll
                    for (int g = 1; g >= 0; --g) {
                        mbar_wait_b(BAR_SFULL(sb, 2 * g + p), par);
                        if (el) { fence_async_smem(); tma_store(tm, kown + p * 64, m * 128 + g * 64, src + p * 16384 + g * 8192); }
                    }
                    TX(10 + t * 8 + p * 4);
                    if (el) { bulk_commit(); bulk_wait_all(); }
                    __syncwarp();
                    TX(11 + t * 8 + p * 4);
                    if (p && ring && lane < 4) asm volatile("{\n.reg .b32 r;\nmapa.shared::cluster.u32 r, %0, %1;\nmbarrier.arrive.shared::cluster.b64 _, [r];\n}" :: "r"(BAR_EMPTY(sb, 5)), "r"(lane & 1) : "memory");
                    uint32_t one = 1;
                    if (LSUB && p) {
                        const __nv_bfloat16* const line = (t ? pt.o : pt.h1) + (m * 128 + lane) * D_ + kown + 64;
                        uint32_t v[4];
#pragma unroll
                        for (int i = 0; i < 4; ++i) asm volatile("ld.relaxed.gpu.global.u32 %0, [%1];" : "=r"(v[i]) : "l"(line + i * 32 * D_) : "memory");
                        one += __ballot_sync(0xffffffffu, (v[0] | v[1] | v[2] | v[3]) != 0) & blockIdx.y;
                    } else {
                        if (el) {
                            mbar_expect_tx(BAR_ONE(sb, EV_BACK), 2048);
#pragma unroll
                            for (int i = 0; i < 4; ++i) tma_load(sb + OFF_JUNK, tm + 2, kown + p * 64, m * 128 + i * 32, BAR_ONE(sb, EV_BACK));
                        }
                        mbar_wait_b(BAR_ONE(sb, EV_BACK), LSUB ? par : p);
                    }
                    if (el) asm volatile("red.relaxed.gpu.global.add.u32 [%0], %1;" :: "l"(g_flags + m * 64 + 16 + t * 16 + 2 * j + p), "r"(one) : "memory");
                    TX(12 + t * 8 + p * 4);
                    if (el && !p) TS(43 + t);
                }
                par ^= 1;
            };
            auto gate = [&](int vec, int ev) {
                uint2 a, b; uint32_t n = 0;
                const uint2* src = g_mod + vec * 512 + j * 64 + (lane >> 2) * 8 + (lane & 3);
                while (true) {
                    a = ld_pkt(src); b = ld_pkt(src + 4);
                    if (__all_sync(0xffffffffu, a.y == ep && b.y == ep)) break;
                    SPIN_GUARD(n); __nanosleep(300);
                }
                sts128(sb + OFF_TAB + (ev - EV_GA) * 512 + lane * 16, a.x << 16, a.x & 0xFFFF0000u, b.x << 16, b.x & 0xFFFF0000u);
                __syncwarp();
                if (el) mbar_arrive(BAR_ONE(sb, ev));
            };
            if (lane < 5) prefetch_map(&mp.h1s + lane);
            if (w == 0) {
#pragma unroll 1
                for (int t = 0; t < 3; ++t) {
                    send(t ? &mp.os : &mp.h1s, sb + (t == 1 ? OFF_STG : OFF_OWN), t != 1, t);
                    if (t && el) mbar_arrive(BAR_ONE(sb, t == 1 ? EV_P2 : EV_SENT));
                    if (t == 1 && m > 0) {
#pragma unroll 4
                        for (int i = 0; i < 16; ++i) (g_halo + ((m - 1) * 8 + j) * 512 + lane)[i * 32] = make_uint4(0, 0, 0, 0);
                    }
                }
            } else {
                mbar_wait_b(BAR_SFULL(sb, 1), 0); mbar_wait_b(BAR_SFULL(sb, 3), 0);
                auto count = [&](int f) {
                    uint32_t v, n = 0;
                    while (true) {
                        asm volatile("ld.acquire.gpu.global.u32 %0, [%1];" : "=r"(v) : "l"(g_flags + f) : "memory");
                        if ((int32_t)(v - ep * 8) >= 0) break;
                        SPIN_GUARD(n); __nanosleep(500);
                    }
                };
                gate(2, EV_GA);
                count(FL_LN2);
                const uint4 t = __ldcg((const uint4*)(g_par2 + j * 128) + lane);
                sts128(sb + OFF_PAR + lane * 16, t.x, t.y, t.z, t.w);
                __syncwarp();
                if (el) mbar_arrive(BAR_ONE(sb, EV_P2));
                gate(5, EV_GB);
#pragma unroll 1
                for (int p = 0; p < 3; ++p) {
                    mbar_wait_b(BAR_ONE(sb, EV_HB), p & 1);
                    __nanosleep(RESTH);
                    if (el) asm volatile("red.release.gpu.global.add.u32 [%0], 1;" :: "l"(g_flags + m * 64 + p) : "memory");
                    count(m * 64 + p);
                    if (el) mbar_arrive(BAR_ONE(sb, EV_H + p));
                }
            }
            cluster_arrive_early = true;
            cluster_arrive();
            mbar_wait_b(BAR_SFULL(sb, w * 2), 1);
        }
        __syncwarp();
    }
    if (aux || (wg == 2 && !cluster_arrive_early)) cluster_arrive();
    cluster_wait();
    if (tid == 0) {
        flag_add(pt.mail->flags + FL_DONE);
    }
}

typedef CUresult (*EncodeFn)(CUtensorMap*, CUtensorMapDataType, cuuint32_t, void*, const cuuint64_t*, const cuuint64_t*, const cuuint32_t*,
                             const cuuint32_t*, CUtensorMapInterleave, CUtensorMapSwizzle, CUtensorMapL2promotion, CUtensorMapFloatOOBfill);

void make_map(EncodeFn fn, CUtensorMap* m, const void* ptr, uint64_t rows, uint64_t cols, uint32_t brows, uint32_t bcols) {
    cuuint64_t dims[2] = {cols, rows}, strides[1] = {cols * 2};
    cuuint32_t box[2] = {bcols, brows}, es[2] = {1, 1};
    fn(m, CU_TENSOR_MAP_DATA_TYPE_BFLOAT16, 2, (void*)ptr, dims, strides, box, es, CU_TENSOR_MAP_INTERLEAVE_NONE,
       bcols == 64 ? CU_TENSOR_MAP_SWIZZLE_128B : bcols == 32 ? CU_TENSOR_MAP_SWIZZLE_64B : CU_TENSOR_MAP_SWIZZLE_NONE, CU_TENSOR_MAP_L2_PROMOTION_L2_256B, CU_TENSOR_MAP_FLOAT_OOB_FILL_NONE);
}
struct View { uint64_t dim[5], stride[4]; uint32_t box[5]; };
void make_view(EncodeFn fn, CUtensorMap* m, const void* ptr, uint32_t rank, const View& v) {
    cuuint64_t dims[5], strides[4];
    cuuint32_t box[5], es[5] = {1, 1, 1, 1, 1};
    for (int i = 0; i < 5; ++i) { dims[i] = v.dim[i]; box[i] = v.box[i]; if (i < 4) strides[i] = v.stride[i] * 2; }
    fn(m, CU_TENSOR_MAP_DATA_TYPE_BFLOAT16, rank, (void*)ptr, dims, strides, box, es, CU_TENSOR_MAP_INTERLEAVE_NONE,
       box[0] == 64 ? CU_TENSOR_MAP_SWIZZLE_128B : CU_TENSOR_MAP_SWIZZLE_64B, CU_TENSOR_MAP_L2_PROMOTION_L2_256B, CU_TENSOR_MAP_FLOAT_OOB_FILL_NONE);
}

}

extern "C" void kernel_launch(void* const* d_in, const int* in_sizes, int n_in, void* d_out, int out_size) {
    (void)in_sizes; (void)n_in; (void)out_size;
    void* fnp = nullptr;
    cudaDriverEntryPointQueryResult qr;
    cudaGetDriverEntryPoint("cuTensorMapEncodeTiled", &fnp, cudaEnableDefault, &qr);
    EncodeFn fn = (EncodeFn)fnp;
    void *h1, *o, *hb, *mail;
    cudaGetSymbolAddress(&h1, g_h1);
    cudaGetSymbolAddress(&mail, g_mail);
    cudaGetSymbolAddress(&o, g_o);
    cudaGetSymbolAddress(&hb, g_hb);
    Maps mp;
    auto wmap = [&](int i, const void* p, uint64_t rows, uint64_t cols, uint64_t sec, uint32_t brows, uint32_t bblk, uint32_t bsec) {
        make_view(fn, &mp.ld[i], p, i == L_WMOD ? 4 : 5, View{{64, rows, cols / sec / 64, sec, 1}, {cols, 64, cols / sec, 64}, {64, brows, bblk, bsec, 1}});
    };
    auto amap = [&](int i, const void* p, uint64_t cols, uint32_t bcols) { make_view(fn, &mp.ld[i], p, 4, View{{cols, S_, 1, 1, 1}, {cols, 64, 64, 64}, {bcols, 128, 1, 1, 1}}); };
    wmap(L_WQKV, d_in[1], D_, 3 * D_, 3, 16, 2, 3);
    wmap(L_WKV, d_in[1], D_, 3 * D_, 3, 16, 2, 2);
    wmap(L_WQ, d_in[1], D_, 3 * D_, 3, 64, 1, 1);
    wmap(L_WO, d_in[2], D_, D_, 1, 64, 1, 1);
    wmap(L_WG, d_in[4], D_, F_, 1, 32, 1, 1);
    wmap(L_WU, d_in[5], D_, F_, 1, 32, 1, 1);
    make_view(fn, &mp.ld[L_WD], d_in[6], 5, View{{D_, 2, 4, 4, F_ / 32}, {D_, 8 * D_, 2 * D_, 32 * D_}, {64, 2, 4, 4, 2}});
    wmap(L_WMOD, d_in[8], D_, 6 * D_, 1, 64, 4, 1);
    amap(L_H1, h1, D_, 32); amap(L_H1Q, h1, D_, 64); amap(L_O, o, D_, 64); amap(L_H2, o, D_, 32); amap(L_HB, hb, F_, 64);
    make_view(fn, &mp.ld[L_X], d_in[0], 4, View{{D_, S_ / 2, 2, 1, 1}, {2 * D_, D_, 64, 64}, {64, 64, 2, 1, 1}});
    make_map(fn, &mp.h1s, h1, S_, D_, 64, 64);
    make_map(fn, &mp.os, o, S_, D_, 64, 64);
    make_map(fn, &mp.h1r, h1, S_, D_, 32, 8);
    make_map(fn, &mp.orr, o, S_, D_, 32, 8);
    make_map(fn, &mp.wm, d_in[8], D_, 6 * D_, 128, 64);
    make_map(fn, &mp.out, d_out, S_ / 2, 2 * D_, 16, 64);
    cudaFuncSetAttribute(fused_block_kernel, cudaFuncAttributeMaxDynamicSharedMemorySize, SMEM_BYTES);
    cudaLaunchConfig_t cfg = {};
    cfg.gridDim = dim3(NCTA); cfg.blockDim = dim3(384); cfg.dynamicSmemBytes = SMEM_BYTES; cfg.stream = cudaStreamPerThread;
    cudaLaunchAttribute at[1];
    at[0].id = cudaLaunchAttributeClusterDimension; at[0].val.clusterDim.x = 2; at[0].val.clusterDim.y = 1; at[0].val.clusterDim.z = 1;
    cfg.attrs = at; cfg.numAttrs = 1;
    const Ptrs pt{(const __nv_bfloat16*)d_in[7], (Mail*)mail, (__nv_bfloat16*)hb, (__nv_bfloat16*)h1, (__nv_bfloat16*)o};
    cudaLaunchKernelEx(&cfg, fused_block_kernel, pt, mp);
}
```

```cpp
#include <cuda_runtime.h>
#include <cuda_bf16.h>
#include <cuda.h>
#include <stdint.h>
#include <stddef.h>

#define LAG 3
#define LAGS 2
#define LAGW 3
#define LAGD 3
#define LAGQ 3
#define EARLY 1
#define NQ 6
#define NS 5
#define RC 224
#define RESTH 1000
#define NB0 2
#define EVB EV_PAR
#define EVS EV_WINL
#define GW 4
#define GD 2
#define WP 4
#define SWO 2
#define HEAD 3
#define TRIG 7
#define QA 3

namespace {

constexpr int S_ = 2048, D_ = 1024, F_ = 3584;
constexpr int NCTA = 132;
constexpr int NSLOT = 6;
constexpr uint32_t SLOT = 32768;
constexpr uint32_t OFF_STG = NSLOT * SLOT;
constexpr uint32_t OFF_BAR = OFF_STG + 32768;
constexpr uint32_t OFF_PAR = OFF_BAR + 384;
constexpr uint32_t OFF_TAB = OFF_PAR + 512;
constexpr uint32_t OFF_JUNK = 0u - 1024;
constexpr uint32_t SMEM_BYTES = 1024 + OFF_TAB + 1024;
constexpr int ST_Q = 33, ST_WO = ST_Q + NQ + NS, ST_GU = ST_WO + 16, ST_G1 = ST_GU + 33;
static_assert(ST_GU % (2 * NSLOT) == 0, "");
constexpr uint32_t OFF_OWN = 5 * SLOT;
constexpr uint32_t sweep_order() {
    uint32_t v = 0, n = 0;
    for (uint32_t want = 0; want < (SWO ? 2 : NSLOT); ++want)
        for (int i = 0; i < NS; ++i) { const uint32_t t = ST_WO - NS + i, s = t % NSLOT; if ((SWO ? s >= 4 : s) == want) v |= (s | (t / NSLOT & 1) << 3) << (4 * n++); }
    return v;
}
constexpr uint32_t SWEEP = sweep_order();

constexpr int FL_DONE = 16 * 64, FL_LN2 = 16 * 64 + 1;

enum { L_WQKV, L_WKV, L_WQ, L_WO, L_WG, L_WU, L_WQ1, L_WD, L_WMOD, L_H1, L_H1E, L_H1Q, L_X, L_O, L_H2, L_H2E, L_HB, L_COUNT };
struct Maps {
    CUtensorMap wm, x, h1s, os, h1r, orr, ld[L_COUNT], out;
};

struct Mail {
    uint32_t flags[16 * 64 + 32];
    uint2 mod[6 * D_ / 2];
    uint4 mod1[8 * 2048];
    uint4 st1[8 * S_ / 2];
    uint32_t par2[D_];
    uint4 halo[128 * 512];
};
struct Ptrs { const __nv_bfloat16* c; Mail* mail; __nv_bfloat16* hb; const uint4* sched; };

__device__ __align__(128) Mail g_mail;
__device__ __align__(128) __nv_bfloat16 g_h1[S_ * D_];
__device__ __align__(128) __nv_bfloat16 g_o[S_ * D_];
__device__ __align__(128) __nv_bfloat16 g_hb[S_ * F_];
#define TS(i) do {} while (0)
#define TW(i) do {} while (0)
#define TX(i) do {} while (0)
#define TR(w, n) do {} while (0)

__device__ __forceinline__ uint32_t smem_u32(const void* p) { return (uint32_t)__cvta_generic_to_shared(p); }
__device__ __forceinline__ void mbar_init(uint32_t bar, uint32_t cnt) { asm volatile("mbarrier.init.shared::cta.b64 [%0], %1;" :: "r"(bar), "r"(cnt) : "memory"); }
__device__ __forceinline__ void mbar_expect_tx(uint32_t bar, uint32_t bytes) { asm volatile("mbarrier.arrive.expect_tx.shared::cta.b64 _, [%0], %1;" :: "r"(bar), "r"(bytes) : "memory"); }
__device__ __forceinline__ void mbar_arrive(uint32_t bar) { asm volatile("mbarrier.arrive.shared::cta.b64 _, [%0];" :: "r"(bar) : "memory"); }
__device__ __forceinline__ void mbar_arrive_if0(uint32_t bar, uint32_t z) {
    asm volatile("{\n.reg .pred p;\nsetp.eq.u32 p, %1, 0;\n@p mbarrier.arrive.shared::cta.b64 _, [%0];\n}" :: "r"(bar), "r"(z) : "memory");
}
__device__ __forceinline__ void mbar_wait(uint32_t bar, uint32_t parity) {
    asm volatile("{\n.reg .pred p;\nW_LOOP:\nmbarrier.try_wait.parity.shared::cta.b64 p, [%0], %1;\n@!p bra W_LOOP;\n}" :: "r"(bar), "r"(parity) : "memory");
}
__device__ __forceinline__ void mbar_wait_b(uint32_t bar, uint32_t parity) {
    asm volatile("{\n.reg .pred p;\n.reg .u32 n;\nmov.u32 n, 0;\n"
        "W_LOOP:\nmbarrier.try_wait.parity.shared::cta.b64 p, [%0], %1;\n@p bra W_DONE;\n"
        "add.u32 n, n, 1;\nsetp.lt.u32 p, n, 0x400000;\n@p bra W_LOOP;\ntrap;\nW_DONE:\n}" :: "r"(bar), "r"(parity) : "memory");
}
__device__ __forceinline__ void tma_load(uint32_t dst, const CUtensorMap* m, int c0, int c1, uint32_t bar) {
    asm volatile("cp.async.bulk.tensor.2d.shared::cluster.global.mbarrier::complete_tx::bytes [%0], [%1, {%3, %4}], [%2];"
        :: "r"(dst), "l"(m), "r"(bar), "r"(c0), "r"(c1) : "memory");
}
__device__ __forceinline__ void tma_load4(uint32_t dst, const CUtensorMap* m, int c0, int c1, int c2, uint32_t bar) {
    asm volatile("cp.async.bulk.tensor.4d.shared::cluster.global.mbarrier::complete_tx::bytes [%0], [%1, {%3, %4, %5, %6}], [%2];"
        :: "r"(dst), "l"(m), "r"(bar), "r"(c0), "r"(c1), "r"(c2), "r"(0) : "memory");
}
__device__ __forceinline__ void tma_load5_mc(uint32_t dst, const CUtensorMap* m, int c0, int c1, int c2, int c3, int c4, uint32_t bar) {
    asm volatile("cp.async.bulk.tensor.5d.shared::cluster.global.mbarrier::complete_tx::bytes.multicast::cluster.L2::cache_hint [%0], [%1, {%3, %4, %5, %6, %7}], [%2], %8, %9;"
        :: "r"(dst), "l"(m), "r"(bar), "r"(c0), "r"(c1), "r"(c2), "r"(c3), "r"(c4), "h"((uint16_t)3), "l"(0x12F0000000000000ull) : "memory");
}
__device__ __forceinline__ void tma_store(const CUtensorMap* m, int c0, int c1, uint32_t src) {
    asm volatile("cp.async.bulk.tensor.2d.global.shared::cta.bulk_group [%0, {%2, %3}], [%1];" :: "l"(m), "r"(src), "r"(c0), "r"(c1) : "memory");
}
__device__ __forceinline__ void bulk_commit() { asm volatile("cp.async.bulk.commit_group;" ::: "memory"); }
__device__ __forceinline__ void bulk_wait_read() { asm volatile("cp.async.bulk.wait_group.read 0;" ::: "memory"); }
__device__ __forceinline__ void bulk_wait_all() { asm volatile("cp.async.bulk.wait_group 0;" ::: "memory"); }
__device__ __forceinline__ void fence_async_smem() { asm volatile("fence.proxy.async.shared::cta;" ::: "memory"); }
__device__ __forceinline__ void fence_async_global() { asm volatile("fence.proxy.async.global;" ::: "memory"); }
__device__ __forceinline__ void prefetch_map(const CUtensorMap* m) { asm volatile("prefetch.tensormap [%0];" :: "l"(m) : "memory"); }
__device__ __forceinline__ void wg_fence() { asm volatile("wgmma.fence.sync.aligned;" ::: "memory"); }
__device__ __forceinline__ void wg_commit() { asm volatile("wgmma.commit_group.sync.aligned;" ::: "memory"); }
template <int N> __device__ __forceinline__ void wg_wait() { asm volatile("wgmma.wait_group.sync.aligned %0;" :: "n"(N) : "memory"); }
__device__ __forceinline__ void bar_sync(int id, int n) { asm volatile("bar.sync %0, %1;" :: "r"(id), "r"(n) : "memory"); }
__device__ __forceinline__ void flag_add(uint32_t* f) { asm volatile("red.relaxed.gpu.global.add.u32 [%0], 1;" :: "l"(f) : "memory"); }
__device__ __forceinline__ uint32_t d16(uint32_t addr) { return (addr & 0x3FFFF) >> 4; }
__device__ __forceinline__ uint64_t mk_desc(uint32_t a16, uint32_t off, uint32_t lbo, uint32_t sbo, uint32_t swz) {
    const uint32_t lo = a16 + (off >> 4) + ((lbo >> 4) << 16), hi = (sbo >> 4) | (swz << 30);
    return ((uint64_t)hi << 32) | lo;
}
__device__ __forceinline__ uint32_t pack2(float lo, float hi) {
    uint32_t r; asm("cvt.rn.bf16x2.f32 %0, %1, %2;" : "=r"(r) : "f"(hi), "f"(lo)); return r;
}
__device__ __forceinline__ uint32_t hfma2_bf16(uint32_t a, uint32_t b, uint32_t c) {
    uint32_t r; asm("fma.rn.bf16x2 %0, %1, %2, %3;" : "=r"(r) : "r"(a), "r"(b), "r"(c)); return r;
}
__device__ __forceinline__ float bf_lo(uint32_t v) { return __uint_as_float(v << 16); }
__device__ __forceinline__ float bf_hi(uint32_t v) { return __uint_as_float(v & 0xFFFF0000u); }
__device__ __forceinline__ float bf_round(float x) { return __bfloat162float(__float2bfloat16_rn(x)); }
__device__ __forceinline__ void stsm4(uint32_t addr, uint32_t r0, uint32_t r1, uint32_t r2, uint32_t r3) {
    asm volatile("stmatrix.sync.aligned.m8n8.x4.shared.b16 [%0], {%1, %2, %3, %4};" :: "r"(addr), "r"(r0), "r"(r1), "r"(r2), "r"(r3) : "memory");
}
__device__ __forceinline__ void stsm4t(uint32_t addr, uint32_t r0, uint32_t r1, uint32_t r2, uint32_t r3) {
    asm volatile("stmatrix.sync.aligned.m8n8.x4.trans.shared.b16 [%0], {%1, %2, %3, %4};" :: "r"(addr), "r"(r0), "r"(r1), "r"(r2), "r"(r3) : "memory");
}
__device__ __forceinline__ void ldsm4(uint32_t addr, uint32_t& r0, uint32_t& r1, uint32_t& r2, uint32_t& r3) {
    asm volatile("ldmatrix.sync.aligned.m8n8.x4.shared.b16 {%0, %1, %2, %3}, [%4];" : "=r"(r0), "=r"(r1), "=r"(r2), "=r"(r3) : "r"(addr) : "memory");
}
__device__ __forceinline__ uint32_t movm(uint32_t a) { uint32_t r; asm volatile("movmatrix.sync.aligned.m8n8.trans.b16 %0, %1;" : "=r"(r) : "r"(a)); return r; }
__device__ __forceinline__ void mma16816(float (&c)[4], uint32_t a0, uint32_t a1, uint32_t a2, uint32_t a3, uint32_t b0, uint32_t b1) {
    asm("mma.sync.aligned.m16n8k16.row.col.f32.bf16.bf16.f32 {%0, %1, %2, %3}, {%4, %5, %6, %7}, {%8, %9}, {%0, %1, %2, %3};"
        : "+f"(c[0]), "+f"(c[1]), "+f"(c[2]), "+f"(c[3]) : "r"(a0), "r"(a1), "r"(a2), "r"(a3), "r"(b0), "r"(b1));
}
__device__ __forceinline__ float ex2(float x) { float r; asm("ex2.approx.ftz.f32 %0, %1;" : "=f"(r) : "f"(x)); return r; }
__device__ __forceinline__ float rcp(float x) { float r; asm("rcp.approx.ftz.f32 %0, %1;" : "=f"(r) : "f"(x)); return r; }
__device__ __forceinline__ float rsq(float x) { float r; asm("rsqrt.approx.ftz.f32 %0, %1;" : "=f"(r) : "f"(x)); return r; }
__device__ __forceinline__ float silu_(float x) { return x * rcp(1.f + ex2(-1.4426950408889634f * x)); }
__device__ __forceinline__ void st_pkt(void* p, uint32_t a, uint32_t b) {
    asm volatile("{\n.reg .b64 t;\nmov.b64 t, {%1, %2};\nst.relaxed.gpu.global.b64 [%0], t;\n}" :: "l"(p), "r"(a), "r"(b) : "memory");
}
__device__ __forceinline__ uint2 ld_pkt(const void* p) {
    uint2 v; asm volatile("{\n.reg .b64 t;\nld.relaxed.gpu.global.b64 t, [%2];\nmov.b64 {%0, %1}, t;\n}" : "=r"(v.x), "=r"(v.y) : "l"(p) : "memory"); return v;
}
__device__ __forceinline__ void st_pkt16(void* p, uint32_t a, uint32_t b, uint32_t c, uint32_t d) {
    asm volatile("{\n.reg .b64 t, u;\n.reg .b128 w;\nmov.b64 t, {%1, %2};\nmov.b64 u, {%3, %4};\nmov.b128 w, {t, u};\nst.relaxed.gpu.global.b128 [%0], w;\n}"
        :: "l"(p), "r"(a), "r"(b), "r"(c), "r"(d) : "memory");
}
__device__ __forceinline__ uint4 ld_pkt16(const void* p) {
    uint4 v; asm volatile("{\n.reg .b64 t, u;\n.reg .b128 w;\nld.relaxed.gpu.global.b128 w, [%4];\nmov.b128 {t, u}, w;\nmov.b64 {%0, %1}, t;\nmov.b64 {%2, %3}, u;\n}"
        : "=r"(v.x), "=r"(v.y), "=r"(v.z), "=r"(v.w) : "l"(p) : "memory"); return v;
}
#define SPIN_GUARD(n) do { if (++(n) > (1u << 22)) asm volatile("trap;"); } while (0)
__device__ __forceinline__ uint4 lds128(uint32_t a) { uint4 v; asm volatile("ld.shared.v4.u32 {%0, %1, %2, %3}, [%4];" : "=r"(v.x), "=r"(v.y), "=r"(v.z), "=r"(v.w) : "r"(a) : "memory"); return v; }
__device__ __forceinline__ void sts128(uint32_t a, uint32_t x, uint32_t y, uint32_t z, uint32_t w) { asm volatile("st.shared.v4.u32 [%0], {%1, %2, %3, %4};" :: "r"(a), "r"(x), "r"(y), "r"(z), "r"(w) : "memory"); }
__device__ __forceinline__ uint2 lds64(uint32_t a) { uint2 v; asm volatile("ld.shared.v2.u32 {%0, %1}, [%2];" : "=r"(v.x), "=r"(v.y) : "r"(a) : "memory"); return v; }
__device__ __forceinline__ void sts64(uint32_t a, uint32_t x, uint32_t y) { asm volatile("st.shared.v2.u32 [%0], {%1, %2};" :: "r"(a), "r"(x), "r"(y) : "memory"); }
__device__ __forceinline__ uint32_t lds32(uint32_t a) { uint32_t v; asm volatile("ld.shared.u32 %0, [%1];" : "=r"(v) : "r"(a) : "memory"); return v; }
__device__ __forceinline__ void sts32(uint32_t a, uint32_t v) { asm volatile("st.shared.u32 [%0], %1;" :: "r"(a), "r"(v) : "memory"); }
__device__ __forceinline__ bool elect_one() {
    uint32_t p; asm volatile("{\n.reg .pred q;\nelect.sync _|q, 0xffffffff;\nselp.u32 %0, 1, 0, q;\n}" : "=r"(p)); return p;
}
__device__ __forceinline__ void cluster_arrive() { asm volatile("barrier.cluster.arrive.relaxed.aligned;" ::: "memory"); }
__device__ __forceinline__ void cluster_wait() { asm volatile("barrier.cluster.wait.aligned;" ::: "memory"); }

__device__ __forceinline__ void wgmma_n128_z(float (&d)[64], uint64_t da, uint64_t db) {
    asm volatile("{\n.reg .pred p;\nsetp.ne.b32 p, 0, 0;\n"
        "wgmma.mma_async.sync.aligned.m64n128k16.f32.bf16.bf16 {"
        "%0, %1, %2, %3, %4, %5, %6, %7, %8, %9, %10, %11, %12, %13, %14, %15, "
        "%16, %17, %18, %19, %20, %21, %22, %23, %24, %25, %26, %27, %28, %29, %30, %31, "
        "%32, %33, %34, %35, %36, %37, %38, %39, %40, %41, %42, %43, %44, %45, %46, %47, "
        "%48, %49, %50, %51, %52, %53, %54, %55, %56, %57, %58, %59, %60, %61, %62, %63"
        "}, %64, %65, p, 1, 1, 0, 1;\n}\n"
        : "=f"(d[0]), "=f"(d[1]), "=f"(d[2]), "=f"(d[3]), "=f"(d[4]), "=f"(d[5]), "=f"(d[6]), "=f"(d[7]),
          "=f"(d[8]), "=f"(d[9]), "=f"(d[10]), "=f"(d[11]), "=f"(d[12]), "=f"(d[13]), "=f"(d[14]), "=f"(d[15]),
          "=f"(d[16]), "=f"(d[17]), "=f"(d[18]), "=f"(d[19]), "=f"(d[20]), "=f"(d[21]), "=f"(d[22]), "=f"(d[23]),
          "=f"(d[24]), "=f"(d[25]), "=f"(d[26]), "=f"(d[27]), "=f"(d[28]), "=f"(d[29]), "=f"(d[30]), "=f"(d[31]),
          "=f"(d[32]), "=f"(d[33]), "=f"(d[34]), "=f"(d[35]), "=f"(d[36]), "=f"(d[37]), "=f"(d[38]), "=f"(d[39]),
          "=f"(d[40]), "=f"(d[41]), "=f"(d[42]), "=f"(d[43]), "=f"(d[44]), "=f"(d[45]), "=f"(d[46]), "=f"(d[47]),
          "=f"(d[48]), "=f"(d[49]), "=f"(d[50]), "=f"(d[51]), "=f"(d[52]), "=f"(d[53]), "=f"(d[54]), "=f"(d[55]),
          "=f"(d[56]), "=f"(d[57]), "=f"(d[58]), "=f"(d[59]), "=f"(d[60]), "=f"(d[61]), "=f"(d[62]), "=f"(d[63])
        : "l"(da), "l"(db));
}
__device__ __forceinline__ void wgmma_n128(float (&d)[64], uint64_t da, uint64_t db) {
    asm volatile("{\n.reg .pred p;\nsetp.eq.b32 p, 0, 0;\n"
        "wgmma.mma_async.sync.aligned.m64n128k16.f32.bf16.bf16 {"
        "%0, %1, %2, %3, %4, %5, %6, %7, %8, %9, %10, %11, %12, %13, %14, %15, "
        "%16, %17, %18, %19, %20, %21, %22, %23, %24, %25, %26, %27, %28, %29, %30, %31, "
        "%32, %33, %34, %35, %36, %37, %38, %39, %40, %41, %42, %43, %44, %45, %46, %47, "
        "%48, %49, %50, %51, %52, %53, %54, %55, %56, %57, %58, %59, %60, %61, %62, %63"
        "}, %64, %65, p, 1, 1, 0, 1;\n}\n"
        : "+f"(d[0]), "+f"(d[1]), "+f"(d[2]), "+f"(d[3]), "+f"(d[4]), "+f"(d[5]), "+f"(d[6]), "+f"(d[7]),
          "+f"(d[8]), "+f"(d[9]), "+f"(d[10]), "+f"(d[11]), "+f"(d[12]), "+f"(d[13]), "+f"(d[14]), "+f"(d[15]),
          "+f"(d[16]), "+f"(d[17]), "+f"(d[18]), "+f"(d[19]), "+f"(d[20]), "+f"(d[21]), "+f"(d[22]), "+f"(d[23]),
          "+f"(d[24]), "+f"(d[25]), "+f"(d[26]), "+f"(d[27]), "+f"(d[28]), "+f"(d[29]), "+f"(d[30]), "+f"(d[31]),
          "+f"(d[32]), "+f"(d[33]), "+f"(d[34]), "+f"(d[35]), "+f"(d[36]), "+f"(d[37]), "+f"(d[38]), "+f"(d[39]),
          "+f"(d[40]), "+f"(d[41]), "+f"(d[42]), "+f"(d[43]), "+f"(d[44]), "+f"(d[45]), "+f"(d[46]), "+f"(d[47]),
          "+f"(d[48]), "+f"(d[49]), "+f"(d[50]), "+f"(d[51]), "+f"(d[52]), "+f"(d[53]), "+f"(d[54]), "+f"(d[55]),
          "+f"(d[56]), "+f"(d[57]), "+f"(d[58]), "+f"(d[59]), "+f"(d[60]), "+f"(d[61]), "+f"(d[62]), "+f"(d[63])
        : "l"(da), "l"(db));
}
__device__ __forceinline__ void wgmma_n256_z(float (&d)[128], uint64_t da, uint64_t db) {
    asm volatile("{\n.reg .pred p;\nsetp.ne.b32 p, 0, 0;\n"
        "wgmma.mma_async.sync.aligned.m64n256k16.f32.bf16.bf16 {"
        "%0, %1, %2, %3, %4, %5, %6, %7, %8, %9, %10, %11, %12, %13, %14, %15, "
        "%16, %17, %18, %19, %20, %21, %22, %23, %24, %25, %26, %27, %28, %29, %30, %31, "
        "%32, %33, %34, %35, %36, %37, %38, %39, %40, %41, %42, %43, %44, %45, %46, %47, "
        "%48, %49, %50, %51, %52, %53, %54, %55, %56, %57, %58, %59, %60, %61, %62, %63, "
        "%64, %65, %66, %67, %68, %69, %70, %71, %72, %73, %74, %75, %76, %77, %78, %79, "
        "%80, %81, %82, %83, %84, %85, %86, %87, %88, %89, %90, %91, %92, %93, %94, %95, "
        "%96, %97, %98, %99, %100, %101, %102, %103, %104, %105, %106, %107, %108, %109, %110, %111, "
        "%112, %113, %114, %115, %116, %117, %118, %119, %120, %121, %122, %123, %124, %125, %126, %127"
        "}, %128, %129, p, 1, 1, 0, 1;\n}\n"
        : "=f"(d[0]), "=f"(d[1]), "=f"(d[2]), "=f"(d[3]), "=f"(d[4]), "=f"(d[5]), "=f"(d[6]), "=f"(d[7]),
          "=f"(d[8]), "=f"(d[9]), "=f"(d[10]), "=f"(d[11]), "=f"(d[12]), "=f"(d[13]), "=f"(d[14]), "=f"(d[15]),
          "=f"(d[16]), "=f"(d[17]), "=f"(d[18]), "=f"(d[19]), "=f"(d[20]), "=f"(d[21]), "=f"(d[22]), "=f"(d[23]),
          "=f"(d[24]), "=f"(d[25]), "=f"(d[26]), "=f"(d[27]), "=f"(d[28]), "=f"(d[29]), "=f"(d[30]), "=f"(d[31]),
          "=f"(d[32]), "=f"(d[33]), "=f"(d[34]), "=f"(d[35]), "=f"(d[36]), "=f"(d[37]), "=f"(d[38]), "=f"(d[39]),
          "=f"(d[40]), "=f"(d[41]), "=f"(d[42]), "=f"(d[43]), "=f"(d[44]), "=f"(d[45]), "=f"(d[46]), "=f"(d[47]),
          "=f"(d[48]), "=f"(d[49]), "=f"(d[50]), "=f"(d[51]), "=f"(d[52]), "=f"(d[53]), "=f"(d[54]), "=f"(d[55]),
          "=f"(d[56]), "=f"(d[57]), "=f"(d[58]), "=f"(d[59]), "=f"(d[60]), "=f"(d[61]), "=f"(d[62]), "=f"(d[63]),
          "=f"(d[64]), "=f"(d[65]), "=f"(d[66]), "=f"(d[67]), "=f"(d[68]), "=f"(d[69]), "=f"(d[70]), "=f"(d[71]),
          "=f"(d[72]), "=f"(d[73]), "=f"(d[74]), "=f"(d[75]), "=f"(d[76]), "=f"(d[77]), "=f"(d[78]), "=f"(d[79]),
          "=f"(d[80]), "=f"(d[81]), "=f"(d[82]), "=f"(d[83]), "=f"(d[84]), "=f"(d[85]), "=f"(d[86]), "=f"(d[87]),
          "=f"(d[88]), "=f"(d[89]), "=f"(d[90]), "=f"(d[91]), "=f"(d[92]), "=f"(d[93]), "=f"(d[94]), "=f"(d[95]),
          "=f"(d[96]), "=f"(d[97]), "=f"(d[98]), "=f"(d[99]), "=f"(d[100]), "=f"(d[101]), "=f"(d[102]), "=f"(d[103]),
          "=f"(d[104]), "=f"(d[105]), "=f"(d[106]), "=f"(d[107]), "=f"(d[108]), "=f"(d[109]), "=f"(d[110]), "=f"(d[111]),
          "=f"(d[112]), "=f"(d[113]), "=f"(d[114]), "=f"(d[115]), "=f"(d[116]), "=f"(d[117]), "=f"(d[118]), "=f"(d[119]),
          "=f"(d[120]), "=f"(d[121]), "=f"(d[122]), "=f"(d[123]), "=f"(d[124]), "=f"(d[125]), "=f"(d[126]), "=f"(d[127])
        : "l"(da), "l"(db));
}
__device__ __forceinline__ void wgmma_n256(float (&d)[128], uint64_t da, uint64_t db) {
    asm volatile("{\n.reg .pred p;\nsetp.eq.b32 p, 0, 0;\n"
        "wgmma.mma_async.sync.aligned.m64n256k16.f32.bf16.bf16 {"
        "%0, %1, %2, %3, %4, %5, %6, %7, %8, %9, %10, %11, %12, %13, %14, %15, "
        "%16, %17, %18, %19, %20, %21, %22, %23, %24, %25, %26, %27, %28, %29, %30, %31, "
        "%32, %33, %34, %35, %36, %37, %38, %39, %40, %41, %42, %43, %44, %45, %46, %47, "
        "%48, %49, %50, %51, %52, %53, %54, %55, %56, %57, %58, %59, %60, %61, %62, %63, "
        "%64, %65, %66, %67, %68, %69, %70, %71, %72, %73, %74, %75, %76, %77, %78, %79, "
        "%80, %81, %82, %83, %84, %85, %86, %87, %88, %89, %90, %91, %92, %93, %94, %95, "
        "%96, %97, %98, %99, %100, %101, %102, %103, %104, %105, %106, %107, %108, %109, %110, %111, "
        "%112, %113, %114, %115, %116, %117, %118, %119, %120, %121, %122, %123, %124, %125, %126, %127"
        "}, %128, %129, p, 1, 1, 0, 1;\n}\n"
        : "+f"(d[0]), "+f"(d[1]), "+f"(d[2]), "+f"(d[3]), "+f"(d[4]), "+f"(d[5]), "+f"(d[6]), "+f"(d[7]),
          "+f"(d[8]), "+f"(d[9]), "+f"(d[10]), "+f"(d[11]), "+f"(d[12]), "+f"(d[13]), "+f"(d[14]), "+f"(d[15]),
          "+f"(d[16]), "+f"(d[17]), "+f"(d[18]), "+f"(d[19]), "+f"(d[20]), "+f"(d[21]), "+f"(d[22]), "+f"(d[23]),
          "+f"(d[24]), "+f"(d[25]), "+f"(d[26]), "+f"(d[27]), "+f"(d[28]), "+f"(d[29]), "+f"(d[30]), "+f"(d[31]),
          "+f"(d[32]), "+f"(d[33]), "+f"(d[34]), "+f"(d[35]), "+f"(d[36]), "+f"(d[37]), "+f"(d[38]), "+f"(d[39]),
          "+f"(d[40]), "+f"(d[41]), "+f"(d[42]), "+f"(d[43]), "+f"(d[44]), "+f"(d[45]), "+f"(d[46]), "+f"(d[47]),
          "+f"(d[48]), "+f"(d[49]), "+f"(d[50]), "+f"(d[51]), "+f"(d[52]), "+f"(d[53]), "+f"(d[54]), "+f"(d[55]),
          "+f"(d[56]), "+f"(d[57]), "+f"(d[58]), "+f"(d[59]), "+f"(d[60]), "+f"(d[61]), "+f"(d[62]), "+f"(d[63]),
          "+f"(d[64]), "+f"(d[65]), "+f"(d[66]), "+f"(d[67]), "+f"(d[68]), "+f"(d[69]), "+f"(d[70]), "+f"(d[71]),
          "+f"(d[72]), "+f"(d[73]), "+f"(d[74]), "+f"(d[75]), "+f"(d[76]), "+f"(d[77]), "+f"(d[78]), "+f"(d[79]),
          "+f"(d[80]), "+f"(d[81]), "+f"(d[82]), "+f"(d[83]), "+f"(d[84]), "+f"(d[85]), "+f"(d[86]), "+f"(d[87]),
          "+f"(d[88]), "+f"(d[89]), "+f"(d[90]), "+f"(d[91]), "+f"(d[92]), "+f"(d[93]), "+f"(d[94]), "+f"(d[95]),
          "+f"(d[96]), "+f"(d[97]), "+f"(d[98]), "+f"(d[99]), "+f"(d[100]), "+f"(d[101]), "+f"(d[102]), "+f"(d[103]),
          "+f"(d[104]), "+f"(d[105]), "+f"(d[106]), "+f"(d[107]), "+f"(d[108]), "+f"(d[109]), "+f"(d[110]), "+f"(d[111]),
          "+f"(d[112]), "+f"(d[113]), "+f"(d[114]), "+f"(d[115]), "+f"(d[116]), "+f"(d[117]), "+f"(d[118]), "+f"(d[119]),
          "+f"(d[120]), "+f"(d[121]), "+f"(d[122]), "+f"(d[123]), "+f"(d[124]), "+f"(d[125]), "+f"(d[126]), "+f"(d[127])
        : "l"(da), "l"(db));
}
template <int O, int L>
__device__ __forceinline__ void wgmma_n64(float (&d)[L], uint64_t da, uint64_t db) {
    asm volatile("{\n.reg .pred p;\nsetp.eq.b32 p, 0, 0;\n"
        "wgmma.mma_async.sync.aligned.m64n64k16.f32.bf16.bf16 {%0, %1, %2, %3, %4, %5, %6, %7, %8, %9, %10, %11, %12, %13, %14, %15, %16, %17, %18, %19, %20, %21, %22, %23, %24, %25, %26, %27, %28, %29, %30, %31}, %32, %33, p, 1, 1, 0, 1;\n}\n"
        : "+f"(d[O + 0]), "+f"(d[O + 1]), "+f"(d[O + 2]), "+f"(d[O + 3]), "+f"(d[O + 4]), "+f"(d[O + 5]), "+f"(d[O + 6]), "+f"(d[O + 7]),
          "+f"(d[O + 8]), "+f"(d[O + 9]), "+f"(d[O + 10]), "+f"(d[O + 11]), "+f"(d[O + 12]), "+f"(d[O + 13]), "+f"(d[O + 14]), "+f"(d[O + 15]),
          "+f"(d[O + 16]), "+f"(d[O + 17]), "+f"(d[O + 18]), "+f"(d[O + 19]), "+f"(d[O + 20]), "+f"(d[O + 21]), "+f"(d[O + 22]), "+f"(d[O + 23]),
          "+f"(d[O + 24]), "+f"(d[O + 25]), "+f"(d[O + 26]), "+f"(d[O + 27]), "+f"(d[O + 28]), "+f"(d[O + 29]), "+f"(d[O + 30]), "+f"(d[O + 31])
        : "l"(da), "l"(db));
}

struct Idx {
    uint32_t lane, warp, w4, q4, g8, prow, pan;
    __device__ __forceinline__ Idx() {
        uint32_t t; asm volatile("mov.u32 %0, %%tid.x;" : "=r"(t));
        lane = t & 31; warp = t >> 5; w4 = warp & 3; q4 = lane & 3; g8 = lane >> 2;
        prow = w4 * 16 + ((lane >> 3) & 1) * 8 + (lane & 7);
        pan = prow * 128 + (((lane >> 4) ^ (lane & 7)) << 4);
    }
};
#define IDX() const Idx ix; const uint32_t lane = ix.lane, warp = ix.warp, w4 = ix.w4, q4 = ix.q4, g8 = ix.g8, prow = ix.prow, pan_addr = ix.pan; \
    (void)lane; (void)warp; (void)w4; (void)q4; (void)g8; (void)prow; (void)pan_addr;

struct Ring {
    uint32_t slot, par;
    __device__ __forceinline__ void next() { if (++slot == NSLOT) { slot = 0; par ^= 1; } }
};
__device__ __forceinline__ uint32_t BAR_FULL(uint32_t sb, uint32_t s) { return sb + OFF_BAR + 8 * s; }
__device__ __forceinline__ uint32_t BAR_EMPTY(uint32_t sb, uint32_t s) { return sb + OFF_BAR + 48 + 8 * s; }
__device__ __forceinline__ uint32_t BAR_SFULL(uint32_t sb, uint32_t i) { return sb + OFF_BAR + 96 + 8 * i; }
__device__ __forceinline__ uint32_t BAR_ONE(uint32_t sb, uint32_t i) { return sb + OFF_BAR + 128 + 8 * i; }
enum { EV_X, EV_X1, EV_WIN, EV_WINL = EV_WIN + WP - 1, EV_GA, EV_GB, EV_P2, EV_LAG0, EV_LAG1, EV_LAG2, EV_LAG3, EV_LAG4, EV_LAG5, EV_HB, EV_H, EV_H1, EV_H2, EV_SENT, EV_SEC, EV_BACK, EV_BACK1, EV_A0, EV_A0L = EV_A0 + 3, EV_PAR, EV_COUNT };

static_assert(128 + 8 * EV_COUNT <= 384, "");

enum { K_ABS, K_OWN, K_PANEL };
enum { F_WRAP = 1, F_TWICE = 2, F_SKIP = 4, F_EARLY = 8 };
constexpr uint32_t pre_ev(uint32_t ev) { return 128 + 8 * ev; }
constexpr uint32_t pre_sfull(uint32_t i, uint32_t par) { return 96 + 8 * i + par; }
constexpr uint4 seg(uint32_t n, uint32_t kind, uint32_t a, uint32_t step, uint32_t q, uint32_t jump, uint32_t flags, uint32_t map, uint32_t kb, uint32_t pre = 0,
                    uint32_t blkj = 0, uint32_t blk = 0, uint32_t split = 0, uint32_t cnt = 0) {
    return uint4{n | (127 + q) / q << 8 | flags << 16 | map << 24, kind | a << 2 | step << 16 | jump / 64 << 24, kb | blkj << 8 | blk << 12 | split << 20, pre | cnt << 24};
}
constexpr int NSEG = 14;
__device__ const uint4 g_sched[3][NSEG] = {
    {seg(NSLOT, K_ABS, 0, 0, 1, 0, F_SKIP, L_WQKV, 0),
     seg(27 - 2 * NQ, K_PANEL, 1, 32, 2, 64, 0, L_WQKV, 24, 0, 2, 0, 1), seg(2 * NQ, K_PANEL, 28 - 2 * NQ, 32, 2, 64, 0, L_WKV, 16, 0, 2, 0, 1),
     seg(NQ, K_PANEL, 28 - 2 * NQ, 64, 1, 64, 0, L_WQ, 16, 0, 2, 0, 3), seg(NS, K_PANEL, 28 - 2 * NQ - 2 * NS, 64, 1, 64, 0, L_WQ1, 8, 0, 2, 1, 4),
     seg(2, K_OWN, 0, 64, 32, 0, 0, L_WO, 16, 0, 2, 0, 3), seg(14, K_PANEL, 0, 64, 1, 64, 0, L_WO, 16, 0, 2, 0, 3),
     seg(4, K_OWN, 0, 32, 32, 0, F_TWICE, L_WG, 24, 0, 7, 0, 2), seg(28, K_PANEL, 0, 32, 2, 64, F_WRAP, L_WG, 24, 0, 7, 0, 2),
     seg(32, K_ABS, 0, 32, 32, 0, 0, L_WG, 16, 0, 7, 3, 2), seg(32, K_ABS, 0, 32, 32, 0, 0, L_WG, 16, 0, 7, 5, 2),
     seg(24, K_ABS, 0, 64, 3, 256, 0, L_WD, 16, 0, 2, 0, 3), seg(16, K_ABS, 6, 64, 2, 320, 0, L_WD, 16, 0, 2, 0, 3), seg(16, K_ABS, 10, 64, 2, 320, 0, L_WD, 16, 0, 2, 0, 3)},
    {seg(28, K_PANEL, 0, 32, 2, 64, F_EARLY, L_H1, 8, pre_sfull(2, 0), 0, 0, 0, 1),
     seg(NQ, K_PANEL, 28 - 2 * NQ, 64, 1, 64, 0, L_H1Q, 16), seg(NS, K_PANEL, 28 - 2 * NQ - 2 * NS, 64, 1, 64, 0, L_H1Q, 16),
     seg(2, K_OWN, 0, 64, 32, 0, 0, L_X, 16), seg(14, K_PANEL, 0, 64, 1, 64, 0, L_O, 16, pre_sfull(0, 1), 0, 0, 0, 2),
     seg(28, K_PANEL, 0, 32, 2, 64, F_EARLY, L_H2, 8, pre_sfull(2, 0), 0, 0, 0, 3),
     seg(32, K_ABS, 0, 32, 32, 0, 0, L_H2, 8, pre_ev(EV_SENT)), seg(32, K_ABS, 0, 32, 32, 0, 0, L_H2, 8),
     seg(24, K_ABS, 0, 64, 3, 256, 0, L_HB, 16, pre_ev(EV_H)), seg(16, K_ABS, 6, 64, 2, 320, 0, L_HB, 16, pre_ev(EV_H1)), seg(16, K_ABS, 10, 64, 2, 320, 0, L_HB, 16, pre_ev(EV_H2))},
    {seg(16, K_ABS, 0, 64, 32, 0, 0, L_WMOD, 32, 0, 4, 32), seg(16, K_ABS, 0, 64, 32, 0, 0, L_WMOD, 32, 0, 4, 48),
     seg(16, K_ABS, 0, 64, 32, 0, 0, L_WMOD, 32, 0, 4, 64), seg(16, K_ABS, 0, 64, 32, 0, 0, L_WMOD, 32, 0, 4, 80)}};

struct Pipe {
    uint32_t sb, slot, par, tok, rel;
    __device__ __forceinline__ void arm() {
        uint32_t t, a; asm volatile("mov.u32 %0, %%tid.x;" : "=r"(t));
        asm("mapa.shared::cluster.u32 %0, %1, %2;" : "=r"(a) : "r"(BAR_EMPTY(sb, 0)), "r"((t >> 5) & 1));
        tok = __shfl_sync(0xffffffffu, (t & 95u) == 0 ? a : 0, t & 31);
    }
    __device__ __forceinline__ uint32_t stage() {
        mbar_wait(BAR_FULL(sb, slot), par);
        return d16(sb) + slot * (SLOT >> 4);
    }
    __device__ __forceinline__ void release() { if (rel) asm volatile("mbarrier.arrive.shared::cluster.b64 _, [%0];" :: "r"(rel) : "memory"); rel = 0; }
    __device__ __forceinline__ void issued() {
        wg_commit(); wg_wait<1>(); release();
        if (tok) rel = tok + 8 * slot;
        if (++slot == NSLOT) { slot = 0; par ^= 1; }
    }
    __device__ __forceinline__ void drain() { wg_wait<0>(); release(); }
    __device__ __forceinline__ void at(int stage) { slot = stage % NSLOT; par = (stage / NSLOT) & 1; }
};
enum { M_QKV, M_Q0KV, M_KV, M_GU3, M_GU2 };
template <int MODE, bool ZERO, bool OWN = false>
__device__ __forceinline__ void step32(float (&a256)[128], float (&a128)[64], Pipe& p, uint32_t wg, uint32_t own = 0) {
    constexpr uint32_t KS = MODE < M_KV ? 12288 : MODE == M_KV ? 8192 : 2048, LBO = MODE <= M_KV ? 2048 : 4096;
    constexpr uint32_t O256 = 8192 + (MODE < M_KV ? 4096 : 0), O128 = 8192 + (MODE < M_KV ? 0 : 16384);
    constexpr bool W128 = MODE == M_QKV || MODE == M_GU3;
    const uint32_t st = p.stage();
    wg_fence();
#pragma unroll
    for (int k = 0; k < 2; ++k) {
        const uint64_t da = OWN ? mk_desc(own, k * 32, 16, 1024, 1) : mk_desc(st + wg * 256, k * 32, 16, 512, 2);
        const uint64_t d0 = mk_desc(st, O256 + k * KS, LBO, 1024, 1), d1 = mk_desc(st, O128 + k * KS, LBO, 1024, 1);
        if (ZERO && k == 0) { wgmma_n256_z(a256, da, d0); if (W128) wgmma_n128_z(a128, da, d1); }
        else { wgmma_n256(a256, da, d0); if (W128) wgmma_n128(a128, da, d1); if (MODE == M_Q0KV) wgmma_n64<0>(a128, da, d1); }
    }
    p.issued();
}
struct Nop { __device__ __forceinline__ void operator()() const {} };
template <bool ZERO, class F = Nop>
__device__ __forceinline__ void step64(float (&acc)[64], Pipe& p, uint32_t wg, int own = -1, F landed = F()) {
    const uint32_t st = p.stage();
    landed();
    const uint32_t sa = own >= 0 ? d16(p.sb) + OFF_STG / 16 + wg * 512 + own * 1024 : st + wg * 512;
    wg_fence();
#pragma unroll
    for (int k = 0; k < 4; ++k) {
        const uint64_t da = mk_desc(sa, k * 32, 16, 1024, 1), db = mk_desc(st, 16384 + k * 2048, 8192, 1024, 1);
        if (ZERO && k == 0) wgmma_n128_z(acc, da, db); else wgmma_n128(acc, da, db);
    }
    p.issued();
}
__device__ __forceinline__ void run64_landed(float (&acc)[64], Pipe& p, uint32_t wg, int n) {
#pragma unroll 1
    while (true) {
        const uint32_t st = d16(p.sb) + p.slot * (SLOT >> 4);
        wg_fence();
#pragma unroll
        for (int k = 0; k < 4; ++k) wgmma_n128(acc, mk_desc(st + wg * 512, k * 32, 16, 1024, 1), mk_desc(st, 16384 + k * 2048, 8192, 1024, 1));
        p.issued();
        if (--n == 0) break;
        p.stage();
    }
}
__device__ __forceinline__ void rename(float (&d)[64], const float (&a)[64]) {
#pragma unroll
    for (int i = 0; i < 64; ++i) asm volatile("mov.b32 %0, %1;" : "=f"(d[i]) : "f"(a[i]));
}
template <int MODE, int ST>
__device__ __forceinline__ void run_own(float (&a256)[128], float (&a128)[64], Pipe& p, uint32_t wg) {
    const uint32_t a0 = d16(p.sb) + OFF_OWN / 16 + wg * 512;
    p.at(ST);
    step32<MODE, true, true>(a256, a128, p, wg, a0);
#pragma unroll 1
    for (int i = 1; i < 4; ++i) step32<MODE, false, true>(a256, a128, p, wg, a0 + (i >> 1) * 1024 + (i & 1) * 4);
    p.drain();
    mbar_arrive_if0(BAR_FULL(p.sb, 5), threadIdx.x & 127);
#pragma unroll 1
    for (int i = 0; i < 4; ++i) {
        if (i < 2) p.at(i ? ST + 6 : ST + 4);
        if (wg == 0) mbar_wait(BAR_ONE(p.sb, EV_A0 + i), ST > 0);
        step32<MODE, false>(a256, a128, p, wg);
    }
    p.at(ST + 9);
}
template <int LG, class Step>
__device__ __forceinline__ void run(int n, uint32_t wg, uint32_t ev, Step step) {
    const int last = LG ? (wg ? EARLY : LG) : 0;
#pragma unroll 1
    for (int part = 0; ; ++part) {
#pragma unroll 1
        for (int i = part ? last : n - last; i > 0; --i) step();
        if (part || !LG) break;
        mbar_arrive_if0(ev, threadIdx.x ^ 128);
        if (wg == 0) mbar_wait(ev, 0);
    }
}

struct LnRow { float rs0, nm0, rs1, nm1; };
__device__ __forceinline__ void publish_stats(uint4* dst, float s0, float q0, float s1, float q1, uint32_t tag) {
    st_pkt16(dst, (__float_as_uint(s0) & ~3u) | tag, __float_as_uint(s1), __float_as_uint(q0), __float_as_uint(q1));
}
__device__ __forceinline__ LnRow merge_stats(const uint4* src, uint32_t tag) {
    uint4 a, b;
    do { a = ld_pkt16(src); b = ld_pkt16(src + S_ / 2); } while (!__all_sync(0xffffffffu, (a.x & b.x & tag) != 0));
    float v[4] = {__uint_as_float(a.x) + __uint_as_float(b.x), __uint_as_float(a.y) + __uint_as_float(b.y),
                  __uint_as_float(a.z) + __uint_as_float(b.z), __uint_as_float(a.w) + __uint_as_float(b.w)};
#pragma unroll
    for (int o = 1; o < 4; o <<= 1)
#pragma unroll
        for (int i = 0; i < 4; ++i) v[i] += __shfl_xor_sync(0xffffffffu, v[i], o);
    const float m0 = v[0] * (1.f / D_), m1 = v[1] * (1.f / D_);
    const float r0 = rsq(fmaxf(fmaf(-m0, m0, v[2] * (1.f / D_)), 0.f) + 1e-5f), r1 = rsq(fmaxf(fmaf(-m1, m1, v[3] * (1.f / D_)), 0.f) + 1e-5f);
    return LnRow{r0, -m0 * r0, r1, -m1 * r1};
}
__device__ __forceinline__ void ln_norm(uint32_t (&y)[32], const float (&x)[64], const LnRow& n) {
#pragma unroll
    for (int e = 0; e < 32; ++e) {
        const float rs = (e & 1) ? n.rs1 : n.rs0, nm = (e & 1) ? n.nm1 : n.nm0;
        y[e] = pack2(fmaf(x[2 * e], rs, nm), fmaf(x[2 * e + 1], rs, nm));
    }
}
__device__ __forceinline__ void ln_emit(const uint32_t (&y)[32], const uint4 (&p)[8], uint32_t sb, uint32_t wg, const Idx& ix) {
#pragma unroll
    for (int i = 0; i < 8; ++i) {
        uint32_t r[4];
#pragma unroll
        for (int e = 0; e < 4; ++e) r[e] = hfma2_bf16(y[4 * i + e], e < 2 ? p[i].z : p[i].w, e < 2 ? p[i].x : p[i].y);
        stsm4(sb + OFF_OWN + wg * 8192 + (i >> 2) * 16384 + (ix.pan ^ ((i & 3) << 5)), r[0], r[1], r[2], r[3]);
        if (i == 3) { __syncwarp(); if (ix.lane == 0) mbar_arrive(BAR_SFULL(sb, wg * 2)); }
    }
    fence_async_smem();
    __syncwarp();
    if (ix.lane == 0) mbar_arrive(BAR_SFULL(sb, wg * 2 + 1));
    bar_sync(1 + wg, 128);
}
template <int P>
__device__ __forceinline__ void load_panel(uint32_t (&r)[32], uint32_t p) {
    IDX();
#pragma unroll
    for (int i = 4 * P; i < 4 * P + 4; ++i) ldsm4(p + (pan_addr ^ ((i & 3) << 5)), r[4 * i], r[4 * i + 1], r[4 * i + 2], r[4 * i + 3]);
}
template <int E0 = 0, int E1 = 32>
__device__ __forceinline__ void widen(float (&x)[64], const uint32_t (&r)[32]) {
#pragma unroll
    for (int e = E0; e < E1; ++e) asm volatile("shl.b32 %0, %2, 16;\nand.b32 %1, %2, 0xFFFF0000;" : "=&f"(x[2 * e]), "=f"(x[2 * e + 1]) : "r"(r[e]));
}
template <int I0 = 0, int I1 = 8>
__device__ __forceinline__ void load_table(uint4 (&t)[8], uint32_t tab) {
#pragma unroll
    for (int i = I0; i < I1; ++i) t[i] = lds128(tab + i * 64 + (threadIdx.x & 3) * 16);
}
template <int STRIDE, class Step>
__device__ __forceinline__ void epilogue_operands(float (&x)[64], uint4 (&g)[8], uint32_t (&r)[32], uint32_t src, uint32_t tab, int first, Step step) {
#pragma unroll
    for (int i = 0; i < 64; ++i) asm volatile("" : "=f"(x[i]));
#pragma unroll
    for (int i = 0; i < 8; ++i) asm volatile("" : "=r"(g[i].x), "=r"(g[i].y), "=r"(g[i].z), "=r"(g[i].w));
#pragma unroll 1
    for (int it = first * STRIDE; it < 8 * STRIDE; ++it) {
        step([&] {
            if (it == 0) load_panel<0>(r, src);
            if (it == STRIDE) load_panel<1>(r, src + 16384);
            if (it == 6 * STRIDE) load_table<0, 4>(g, tab);
            if (it == 7 * STRIDE) load_table<4, 8>(g, tab);
        });
        if (it == 2 * STRIDE) widen<0, 8>(x, r);
        if (it == 3 * STRIDE) widen<8, 16>(x, r);
        if (it == 4 * STRIDE) widen<16, 24>(x, r);
        if (it == 5 * STRIDE) widen<24, 32>(x, r);
    }
}
__device__ __forceinline__ float gate_of(const uint4 (&t)[8], int e) {
    const uint4 v = t[e >> 3];
    return __uint_as_float((e & 4) ? ((e & 1) ? v.w : v.z) : ((e & 1) ? v.y : v.x));
}
__device__ __forceinline__ constexpr int glu_at(int i, int e) { return (i >> 2) * 64 + ((i >> 1) & 1) * 16 + (e >> 1) * 4 + (i & 1) * 2 + (e & 1); }
struct Raw { const float (&a)[64]; __device__ __forceinline__ float operator()(int e) const { return a[e]; } };
struct Packed {
    const uint32_t (&a)[64];
    __device__ __forceinline__ float operator()(int e) const {
        float v;
        if (e & 1) asm volatile("and.b32 %0, %1, 0xFFFF0000;" : "=f"(v) : "r"(a[e >> 1])); else asm volatile("shl.b32 %0, %1, 16;" : "=f"(v) : "r"(a[e >> 1]));
        return v;
    }
};
template <class A>
__device__ __forceinline__ void glu_tanh(float (&t)[8], A a, int i) {
#pragma unroll
    for (int e = 0; e < 8; ++e) asm volatile("tanh.approx.f32 %0, %1;" : "=f"(t[e]) : "f"(a(glu_at(i, e))));
}
template <bool FENCE, class A>
__device__ __forceinline__ void glu_store(const float (&t)[8], A a, int i, __nv_bfloat16* dst) {
    uint32_t r[4];
#pragma unroll
    for (int c = 0; c < 4; ++c) {
        const float u0 = a(32 + glu_at(i, 2 * c)), u1 = a(33 + glu_at(i, 2 * c));
        r[c] = pack2(fmaf(t[2 * c], u0, u0), fmaf(t[2 * c + 1], u1, u1));
    }
    if (!FENCE) asm volatile("st.global.v4.u32 [%0], {%1, %2, %3, %4};" :: "l"(dst + (i & 1) * 8 * F_ + (i >> 1) * 32), "r"(r[0]), "r"(r[1]), "r"(r[2]), "r"(r[3]) : "memory");
    else asm volatile("{\n.reg .pred p;\nsetp.eq.u32 p, %5, %6;\nG_LOOP:\nst.global.v4.u32 [%0], {%1, %2, %3, %4};\n@p bra G_LOOP;\n}"
        :: "l"(dst + (i & 1) * 8 * F_ + (i >> 1) * 32), "r"(r[0]), "r"(r[1]), "r"(r[2]), "r"(r[3]), "r"(blockIdx.y), "r"(1000 + i) : "memory");
}
__device__ __forceinline__ void glu_now(const float (&a)[64], __nv_bfloat16* dst) {
    float t[2][8];
#pragma unroll
    for (int i = 0; i <= 4; ++i) {
        if (i < 4) glu_tanh(t[i & 1], Raw{a}, i);
        if (i > 0) glu_store<true>(t[(i - 1) & 1], Raw{a}, i - 1, dst);
    }
}
template <class Step>
__device__ __forceinline__ void glu_under(uint32_t (&a)[64], __nv_bfloat16* dst, int n, Step step) {
#pragma unroll 1
    for (int it = -n; it < 16; ++it) {
        step();
        if (it >= 0 && !(it & 1)) {
#pragma unroll
            for (int i = 0; i < 4; ++i)
                if ((it & 7) == 2 * i) {
                    float t[8];
                    glu_tanh(t, Packed{a}, i); glu_store<false>(t, Packed{a}, i, dst);
#pragma unroll
                    for (int c = 0; c < 8; ++c) { const int e = (glu_at(i, (2 * c) & 7) >> 1) + (c >> 2) * 16; a[e] = a[32 + e]; }
                    if (i == 3) dst += 64;
                }
        }
    }
}
__device__ __forceinline__ void pack_all(uint32_t (&d)[64], const float (&a)[128]) {
#pragma unroll
    for (int i = 0; i < 64; ++i) d[i] = pack2(a[2 * i], a[2 * i + 1]);
}

__global__ void __launch_bounds__(384, 1)
fused_block_kernel(const __grid_constant__ Ptrs pt, const __grid_constant__ Maps mp) {
    uint32_t* const g_flags = pt.mail->flags;
    uint2* const g_mod = pt.mail->mod;
    uint4* const g_st1 = pt.mail->st1;
    uint32_t* const g_par2 = pt.mail->par2;
    uint4* const g_halo = pt.mail->halo;
    const __nv_bfloat16* __restrict__ cvec = pt.c;
    if (threadIdx.x == 224) { prefetch_map(&mp.x); prefetch_map(&mp.wm); }
    extern __shared__ __align__(1024) uint8_t smem[];
    const uint32_t sb = smem_u32(smem) + 1024;
    const uint32_t tid = threadIdx.x, tw = tid & 127, lane = tid & 31;
    const uint32_t warp = __shfl_sync(0xffffffffu, tid >> 5, 0), wg = warp >> 2;
    uint32_t rank; asm("mov.u32 %0, %%cluster_ctarank;" : "=r"(rank));
    rank = __shfl_sync(0xffffffffu, rank, 0);
    uint32_t ep;
#define LOAD_EP() asm volatile("ld.relaxed.gpu.global.u32 %0, [%1];" : "=r"(ep) : "l"(&g_flags[FL_DONE + (lane & blockIdx.y)]) : "memory")
    uint32_t smid; asm volatile("mov.u32 %0, %%smid;" : "=r"(smid));
    const int c = __shfl_sync(0xffffffffu, smid >> 1, 0);
    int grp, j;
    if (c < 32) { grp = c & 7; j = c >> 3; }
    else if (c < 60) { grp = 1 + (c - 32) % 7; j = 4 + (c - 32) / 7; }
    else if (c < 62) { grp = -1; j = (c - 60) * 2 + rank; }
    else { grp = 0; j = c - 58; }
    const bool aux = grp < 0;
    const int m = grp * 2 + rank;

    bool cluster_arrive_early = false;
    if (wg < 2) {
      LOAD_EP();
      cluster_arrive();
      if (aux) {
        cluster_wait();
        ep = __shfl_sync(0xffffffffu, ep, 0) / NCTA + 1;
        Ring r{0, 0};
#pragma unroll 1
        for (int p = 0; p < 4; ++p) {
            float acc[64];
#pragma unroll
            for (int i = 0; i < 64; ++i) acc[i] = 0.f;
#pragma unroll 1
            for (int kc = 0; kc < 16; ++kc) {
                mbar_wait(BAR_FULL(sb, r.slot), r.par);
                wg_fence();
#pragma unroll
                for (int k = 0; k < 4; ++k)
                    wgmma_n128(acc, mk_desc(d16(sb) + kc * 64, OFF_STG + k * 32, 16, 0, 1), mk_desc(d16(sb) + r.slot * (SLOT >> 4) + wg * 1024, k * 2048, 8192, 1024, 1));
                wg_commit();
                wg_wait<0>();
                mbar_arrive_if0(BAR_EMPTY(sb, r.slot), tw);
                r.next();
            }
            if (tw < 32) {
                if (tw < 4) {
#pragma unroll
                    for (int jn = 0; jn < 16; ++jn) sts32(sb + OFF_TAB + wg * 256 + (jn * 4 + tw) * 4, pack2(acc[jn * 4], acc[jn * 4 + 1]));
                }
                __syncwarp();
#pragma unroll 1
                for (uint32_t t = wg * 64 + tw; t < wg * 64 + 64; t += 32) {
                    const uint32_t val = lds32(sb + OFF_TAB + t * 4);
                    const float one = p == 2 ? 1.f : 0.f;
                    if (p == 0 || p == 3) st_pkt(g_mod + (8 + p * 4 + j) * 128 + t, val, ep);
                    else g_par2[(j * 16 + (t >> 3)) * 16 + (t & 3) * 4 + (p - 1) * 2 + ((t >> 2) & 1)] = pack2(0.5f * bf_round(one + bf_lo(val)), 0.5f * bf_round(one + bf_hi(val)));
                }
                __syncwarp();
                if (tw == 0 && p == 2) asm volatile("red.release.gpu.global.add.u32 [%0], 1;" :: "l"(&g_flags[FL_LN2]) : "memory");
            }
        }
      } else {
        Pipe pp{sb, 0, 0, 0, 0};
        pp.arm();
        {
            IDX();
            uint4* const st1 = g_st1 + m * 64 + warp * 8 + g8;
            if (q4 == (g8 >> 1)) st_pkt16(st1 + j * (S_ / 2), 0, 0, 0, 0);
            cluster_wait();
            uint32_t xr[32];
            if (w4 == 0) TX(0 + 40 * wg);
            mbar_wait(BAR_ONE(sb, EV_X + wg), 0);
            if (w4 == 0) TX(1 + 40 * wg);
            float sm[4] = {0.f, 0.f, 0.f, 0.f}, g0[4] = {0.f, 0.f, 0.f, 0.f}, g1[4] = {0.f, 0.f, 0.f, 0.f};
#pragma unroll
            for (int i = 0; i < 8; ++i) {
                ldsm4(sb + OFF_STG + wg * 8192 + (i >> 2) * 16384 + (pan_addr ^ ((i & 3) << 5)), xr[4 * i], xr[4 * i + 1], xr[4 * i + 2], xr[4 * i + 3]);
                mma16816(sm, xr[4 * i], xr[4 * i + 1], xr[4 * i + 2], xr[4 * i + 3], 0x3F803F80u, 0x3F803F80u);
                mma16816(g0, xr[4 * i], xr[4 * i + 1], xr[4 * i + 2], xr[4 * i + 3], xr[4 * i], xr[4 * i + 2]);
                mma16816(g1, xr[4 * i], xr[4 * i + 1], xr[4 * i + 2], xr[4 * i + 3], xr[4 * i + 1], xr[4 * i + 3]);
            }
            if (q4 == (g8 >> 1))
                publish_stats(st1 + j * (S_ / 2), sm[0], (g8 & 1) ? g0[1] : g0[0], sm[2], (g8 & 1) ? g1[3] : g1[2], 1);
            if (w4 == 0) TX(2 + 40 * wg);
            float xf[64];
            widen(xf, xr);
            mbar_wait(BAR_ONE(sb, EVS), 0);
            const LnRow n1 = merge_stats(st1 + q4 * S_, 1);
            if (w4 == 0) TX(5 + 40 * wg);
            ln_norm(xr, xf, n1);
            ep = __shfl_sync(0xffffffffu, ep, 0) / NCTA + 1;
            asm volatile("setmaxnreg.inc.sync.aligned.u32 %0;" :: "n"(RC));
            mbar_wait(BAR_ONE(sb, EV_PAR), 0);
            if (w4 == 0) TX(6 + 40 * wg);
            uint4 par[8];
            load_table(par, sb + OFF_PAR);
            ln_emit(xr, par, sb, wg, ix);
            TW(0);
        }
        uint32_t xr[32];
        {
            float qa[64];
            uint32_t kl[16], kh[16], kp[16];
            uint32_t v0[32], v1[32];
            {
                float kv[128];
                float q1[64], q2[64];
                run_own<M_QKV, 0>(kv, q1, pp, wg);
                run<0>(24 - 2 * NS - 2 * NQ, wg, 0, [&] { step32<M_QKV, false>(kv, q1, pp, wg); });
                pp.drain();
                rename(q2, q1);
                run<0>(2 * NS, wg, 0, [&] { step32<M_Q0KV, false>(kv, q2, pp, wg); });
                pp.drain();
                rename(qa, q2);
                run<LAGQ>(2 * NQ, wg, BAR_ONE(sb, EV_LAG0), [&] { step32<M_KV, false>(kv, qa, pp, wg); });
                pp.stage();
                pp.drain();
                TW(1);
                IDX();
#pragma unroll
                for (int t = 0; t < 16; ++t) v1[(t >> 1) * 4 + 2 + (t & 1)] = movm(pack2(kv[66 + 4 * t], kv[67 + 4 * t]));
#pragma unroll
                for (int t = 0; t < 16; ++t) {
                    kl[t] = pack2(kv[4 * t], kv[4 * t + 1]); kh[t] = pack2(kv[4 * t + 2], kv[4 * t + 3]);
                    v1[(t >> 1) * 4 + (t & 1)] = pack2(kv[64 + 4 * t], kv[65 + 4 * t]);
                }
                if (w4 < 3) {
                    const uint32_t dst = sb + OFF_STG + wg * 8192 + (w4 >> 1) * 16384 + (w4 & 1) * 4096;
#pragma unroll
                    for (int i = 0; i < 4; ++i) sts128(dst + i * 512 + lane * 16, kh[4 * i], kh[4 * i + 1], kh[4 * i + 2], kh[4 * i + 3]);
#pragma unroll
                    for (int i = 0; i < 8; ++i) sts64(dst + 2048 + i * 256 + lane * 8, v1[4 * i + 2], v1[4 * i + 3]);
                } else if (m < 15) {
                    uint4* const dst = g_halo + (m * 8 + j) * 512 + wg * 256;
#pragma unroll
                    for (int i = 0; i < 4; ++i) { if (!kh[4 * i]) kh[4 * i] = 0x8000u; st_pkt16(dst + i * 32 + lane, kh[4 * i], kh[4 * i + 1], kh[4 * i + 2], kh[4 * i + 3]); }
#pragma unroll
                    for (int i = 0; i < 8; ++i) { if (!v1[4 * i + 2]) v1[4 * i + 2] = 0x8000u; st_pkt((uint2*)(dst + 128) + i * 32 + lane, v1[4 * i + 2], v1[4 * i + 3]); }
                }
                TW(2);
            }
            pp.at(ST_Q);
            run64_landed(qa, pp, wg, QA);
            pp.stage();
            IDX();
            uint4* const halo = g_halo + ((m - 1) * 8 + j) * 512 + wg * 256;
            auto fetch_halo = [&] {
#pragma unroll
                for (int i = 0; i < 4; ++i) {
                    const uint4 t = m > 0 ? ld_pkt16(halo + i * 32 + lane) : make_uint4(0, 0, 0, 0);
                    kp[4 * i] = t.x; kp[4 * i + 1] = t.y; kp[4 * i + 2] = t.z; kp[4 * i + 3] = t.w;
                }
#pragma unroll
                for (int i = 0; i < 8; ++i) {
                    const uint2 t = m > 0 ? ld_pkt((const uint2*)(halo + 128) + i * 32 + lane) : make_uint2(0, 0);
                    v0[4 * i] = t.x; v0[4 * i + 1] = t.y;
                }
            };
            bar_sync(1 + wg, 128);
#pragma unroll
            for (int t = 0; t < 16; ++t) v1[(t >> 1) * 4 + (t & 1)] = movm(v1[(t >> 1) * 4 + (t & 1)]);
            if (w4 == 0) fetch_halo();
            else {
                const uint32_t src = sb + OFF_STG + wg * 8192 + ((w4 - 1) >> 1) * 16384 + ((w4 - 1) & 1) * 4096;
#pragma unroll
                for (int i = 0; i < 4; ++i) { const uint4 t = lds128(src + i * 512 + lane * 16); kp[4 * i] = t.x; kp[4 * i + 1] = t.y; kp[4 * i + 2] = t.z; kp[4 * i + 3] = t.w; }
#pragma unroll
                for (int i = 0; i < 8; ++i) { const uint2 t = lds64(src + 2048 + i * 256 + lane * 8); v0[4 * i] = t.x; v0[4 * i + 1] = t.y; }
            }
            TW(18);
            pp.at(ST_Q + QA);
            run64_landed(qa, pp, wg, NQ - QA);
#pragma unroll
            for (int t = 0; t < 16; ++t) asm volatile("mov.b32 %0, %1;" : "=r"(v0[(t >> 1) * 4 + 2 + (t & 1)]) : "r"(v1[(t >> 1) * 4 + (t & 1)]));
            bar_sync(1 + wg, 128);
            if (w4 == 0 && m > 0) {
                while (true) {
                    bool ok = true;
#pragma unroll
                    for (int i = 0; i < 8; ++i) ok = ok && v0[4 * i] != 0 && kp[4 * (i & 3)] != 0;
                    if (__all_sync(0xffffffffu, ok)) break;
                    fetch_halo();
                }
            }
            pp.drain();
            float qb[64];
            rename(qb, qa);
            TW(3);
            const bool lo0 = q4 * 2 > g8, lo1 = q4 * 2 + 1 > g8;
            const bool nopast = m == 0 && w4 == 0;
            const uint32_t lomask = (lo0 ? 0xFFFFu : 0u) | (lo1 ? 0xFFFF0000u : 0u);
            const float sl2 = 0.17677669529663687f * 1.4426950408889634f;
            const uint32_t oa = wg * 8192 + (w4 * 16 + (lane & 7)) * 128 + (((lane >> 3) ^ (lane & 7)) << 4);
#pragma unroll
            for (int hp = 0; hp < 2; ++hp) {
                if (hp) {
                    bar_sync(3, 256);
#pragma unroll 1
                    for (int it = 0; it < NS; ++it) {
                        pp.slot = (SWEEP >> (4 * it)) & 7; pp.par = (SWEEP >> (4 * it + 3)) & 1;
                        const uint32_t st = pp.stage();
                        wg_fence();
#pragma unroll
                        for (int k = 0; k < 4; ++k) wgmma_n64<32>(qb, mk_desc(st + wg * 512, k * 32, 16, 1024, 1), mk_desc(st, 16384 + k * 2048, 8192, 1024, 1));
                        pp.issued();
                        if (SWO) {
                            if (it == 0) pp.rel = 0;
                            if (it == SWO && pp.tok) asm volatile("mbarrier.arrive.shared::cluster.b64 _, [%0];" :: "r"(pp.tok + 8 * (SWEEP & 7)) : "memory");
                        }
                    }
                    mbar_wait(BAR_FULL(sb, ST_WO % NSLOT), (ST_WO / NSLOT) & 1);
                    pp.drain();
                    load_panel<0>(xr, sb + ST_WO % NSLOT * SLOT + wg * 8192);
                    TW(4);
                }
                float e0[4], e1[4], mx[4], sum[4];
#pragma unroll
                for (int hh = 0; hh < 2; ++hh) {
                    const int h = 2 * hp + hh;
                    uint32_t qf[8];
                    float s[3][4];
#pragma unroll
                    for (int i = 0; i < 8; ++i) qf[i] = pack2(qb[16 * h + 2 * i], qb[16 * h + 2 * i + 1]);
#pragma unroll
                    for (int nt = 0; nt < 3; ++nt) {
                        const uint32_t (&kk)[16] = nt == 0 ? kp : nt == 1 ? kl : kh;
                        s[nt][0] = s[nt][1] = s[nt][2] = s[nt][3] = 0.f;
                        mma16816(s[nt], qf[0], qf[1], qf[2], qf[3], kk[4 * h], kk[4 * h + 1]);
                        mma16816(s[nt], qf[4], qf[5], qf[6], qf[7], kk[4 * h + 2], kk[4 * h + 3]);
                    }
#pragma unroll
                    for (int hf = 0; hf < 2; ++hf) {
                        e0[2 * hh + hf] = lo0 ? ((hf == 0 && nopast) ? -INFINITY : s[hf][hf * 2]) : s[hf + 1][hf * 2];
                        e1[2 * hh + hf] = lo1 ? ((hf == 0 && nopast) ? -INFINITY : s[hf][hf * 2 + 1]) : s[hf + 1][hf * 2 + 1];
                        mx[2 * hh + hf] = fmaxf(e0[2 * hh + hf], e1[2 * hh + hf]);
                    }
                }
#pragma unroll
                for (int o = 1; o < 4; o <<= 1)
#pragma unroll
                    for (int u = 0; u < 4; ++u) mx[u] = fmaxf(mx[u], __shfl_xor_sync(0xffffffffu, mx[u], o));
#pragma unroll
                for (int u = 0; u < 4; ++u) {
                    const float c = -mx[u] * sl2;
                    e0[u] = ex2(fmaf(e0[u], sl2, c)); e1[u] = ex2(fmaf(e1[u], sl2, c));
                    sum[u] = e0[u] + e1[u];
                }
#pragma unroll
                for (int o = 1; o < 4; o <<= 1)
#pragma unroll
                    for (int u = 0; u < 4; ++u) sum[u] += __shfl_xor_sync(0xffffffffu, sum[u], o);
#pragma unroll
                for (int u = 0; u < 4; ++u) {
                    const int h = 2 * hp + (u >> 1), hf = u & 1;
                    const uint32_t (&vv)[32] = hf ? v1 : v0;
                    const float iv = rcp(sum[u]);
                    const uint32_t pr = pack2(e0[u] * iv, e1[u] * iv);
                    float o[2][4];
#pragma unroll
                    for (int t = 0; t < 2; ++t) {
                        o[t][0] = o[t][1] = o[t][2] = o[t][3] = 0.f;
                        mma16816(o[t], vv[8 * h + 4 * t], vv[8 * h + 4 * t + 1], vv[8 * h + 4 * t + 2], vv[8 * h + 4 * t + 3], pr & lomask, pr & ~lomask);
                    }
                    stsm4t(sb + OFF_STG + hp * 16384 + (oa ^ ((h & 1) << 6)) + hf * 1024, pack2(o[0][0], o[0][1]), pack2(o[0][2], o[0][3]), pack2(o[1][0], o[1][1]), pack2(o[1][2], o[1][3]));
                }
                __syncwarp();
                if (lane == 0) mbar_arrive(BAR_SFULL(sb, wg * 2 + hp));
                if (!hp) TW(19);
            }
            TW(5);
        }
        {
            float acc[64], xf[64];
            uint4 gt[8], par[8];
            fence_async_smem();
            bar_sync(3, 256);
            pp.at(ST_WO);
            mbar_wait(BAR_FULL(sb, (ST_WO + 1) % NSLOT), ((ST_WO + 1) / NSLOT) & 1);
            step64<true>(acc, pp, wg, 0, [&] { load_panel<1>(xr, sb + (ST_WO + 1) % NSLOT * SLOT + wg * 8192); });
            step64<false>(acc, pp, wg, 1);
            fence_async_smem();
            bar_sync(1 + wg, 128);
            mbar_wait(BAR_ONE(sb, EV_GA), 0);
            pp.drain();
            uint4* const pub = g_st1 + __shfl_sync(0xffffffffu, j * (S_ / 2) + m * 64 + (tid >> 2), lane);
            pp.at(ST_WO + 2);
            epilogue_operands<1>(xf, gt, xr, 0, sb + OFF_TAB, 2, [&](auto f) { step64<false>(acc, pp, wg, -1, f); });
            run<LAGW>(8, wg, BAR_ONE(sb, EV_LAG4), [&] { step64<false>(acc, pp, wg); });
            pp.drain();
            TW(6);
            float su[4] = {0.f, 0.f, 0.f, 0.f}, sq[4] = {0.f, 0.f, 0.f, 0.f};
#pragma unroll
            for (int e = 0; e < 64; ++e) {
                xf[e] = fmaf(gate_of(gt, e), acc[e], xf[e]);
                su[e & 3] += xf[e]; sq[e & 3] = fmaf(xf[e], xf[e], sq[e & 3]);
            }
            {
                float v[4] = {su[0] + su[1], sq[0] + sq[1], su[2] + su[3], sq[2] + sq[3]};
#pragma unroll
                for (int o = 1; o < 4; o <<= 1)
#pragma unroll
                    for (int i = 0; i < 4; ++i) v[i] += __shfl_xor_sync(0xffffffffu, v[i], o);
                if ((tid & 3) == 0) publish_stats(pub, v[0], v[1], v[2], v[3], 2);
            }
            IDX();
            mbar_wait(BAR_ONE(sb, EV_P2), 0);
            TW(7);
#pragma unroll
            for (int i = 0; i < 8; ++i)
                stsm4(sb + OFF_STG + wg * 8192 + (i >> 2) * 16384 + (pan_addr ^ ((i & 3) << 5)), pack2(xf[8 * i], xf[8 * i + 1]), pack2(xf[8 * i + 2], xf[8 * i + 3]),
                      pack2(xf[8 * i + 4], xf[8 * i + 5]), pack2(xf[8 * i + 6], xf[8 * i + 7]));
            load_table(par, sb + OFF_PAR);
            mbar_wait(BAR_EMPTY(sb, (ST_GU - 1) % NSLOT), ((ST_GU - 1) / NSLOT) & 1);
            if (warp == 0) TX(8);
            const LnRow n2 = merge_stats(pub + ((int)q4 * 2 - j) * (S_ / 2), 2);
            TW(8);
            ln_norm(xr, xf, n2);
            ln_emit(xr, par, sb, wg, ix);
            TW(9);
        }
        {
            auto h_at = [&](int col) { IDX(); return pt.hb + (m * 128 + warp * 16 + g8) * F_ + j * 448 + col + q4 * 8; };
            uint32_t gu[64];
            {
                float a256[128], a128[64];
                run_own<M_GU3, ST_GU>(a256, a128, pp, wg);
                run<LAG>(24, wg, BAR_ONE(sb, EV_LAG1), [&] { step32<M_GU3, false>(a256, a128, pp, wg); });
                __nv_bfloat16* const dst = h_at(128);
                pp.drain();
                TW(10);
                glu_now(a128, dst);
                pack_all(gu, a256);
                TW(11);
            }
#pragma unroll 1
            for (int p = 0; p < 2; ++p) {
                float b256[128], none[64];
                pp.at(p ? ST_G1 + 32 : ST_G1);
                step32<M_GU2, true>(b256, none, pp, wg);
                glu_under(gu, h_at(p * 192), GW + wg, [&] { step32<M_GU2, false>(b256, none, pp, wg); });
                mbar_arrive_if0(BAR_ONE(sb, EV_HB), lane);
                run<LAGS>(15 - GW - wg, wg, BAR_ONE(sb, EV_LAG2 + p), [&] { step32<M_GU2, false>(b256, none, pp, wg); });
                pp.drain();
                TW(12 + 2 * p);
                pack_all(gu, b256);
                TW(13 + 2 * p);
            }
            float acc[64], xf[64];
            uint4 gt[8];
            pp.at(ST_G1 + 64);
            step64<true>(acc, pp, wg);
            glu_under(gu, h_at(320), GD + wg, [&] { step64<false>(acc, pp, wg); });
            mbar_arrive_if0(BAR_ONE(sb, EV_HB), lane);
            uint32_t x1[32];
#pragma unroll
            for (int i = 0; i < 32; ++i) asm volatile("" : "=r"(x1[i]));
            mbar_wait(BAR_ONE(sb, EV_GB), 0);
            epilogue_operands<2>(xf, gt, x1, sb + OFF_STG + wg * 8192, sb + OFF_TAB + 512, 0, [&](auto f) { step64<false>(acc, pp, wg, -1, f); });
            run<LAGD>(23 - GD - wg, wg, BAR_ONE(sb, EV_LAG5), [&] { step64<false>(acc, pp, wg); });
            cluster_arrive();
            const uint32_t warp_u = warp;
            IDX();
            wg_wait<0>();
            TW(16);
#pragma unroll
            for (int p = 0; p < 2; ++p) {
#pragma unroll
                for (int i = 4 * p; i < 4 * p + 4; ++i) {
                    uint32_t r[4];
#pragma unroll
                    for (int e = 0; e < 4; ++e)
                        r[e] = pack2(fmaf(gate_of(gt, 8 * i + 2 * e), acc[8 * i + 2 * e], xf[8 * i + 2 * e]), fmaf(gate_of(gt, 8 * i + 2 * e + 1), acc[8 * i + 2 * e + 1], xf[8 * i + 2 * e + 1]));
                    stsm4(sb + OFF_STG + wg * 8192 + p * 16384 + (pan_addr ^ ((i & 3) << 5)), r[0], r[1], r[2], r[3]);
                }
                fence_async_smem();
                __syncwarp();
                if (elect_one())
                    tma_store(&mp.out, wg * D_ + j * 128 + p * 64, m * 64 + (warp_u & 3) * 16, sb + OFF_STG + wg * 8192 + p * 16384 + (warp_u & 3) * 2048);
            }
            bulk_commit();
            bulk_wait_read();
            mbar_arrive_if0(BAR_SFULL(sb, wg * 2), lane);
            TW(17);
        }
      }
    } else {
        const bool sil = aux || warp == 9 || warp == 10;
        uint4 cv;
        if (sil) cv = *(const uint4*)(cvec + ((aux ? warp : j) & 3) * 256 + lane * 8);
        LOAD_EP();
        uint4* const modp = pt.mail->mod1 + (lane >> 2) * 2048 + (j & 3) * 512 + ((m * 2 + (j >> 2)) * 4 + (warp & 3)) * 4 + (lane & 3);
        if (!aux) st_pkt16(modp, 0, 0, 0, 0);
        uint4 sg = make_uint4(0, 0, 0, 0);
        if (lane < NSEG) sg = pt.sched[(aux ? 2 : warp == 11) * NSEG + lane];
        auto load_x = [&](int g) {
            mbar_expect_tx(BAR_ONE(sb, EV_X + g), 16384);
#pragma unroll
            for (int i = 0; i < 2; ++i) tma_load(sb + OFF_STG + i * 16384 + g * 8192, &mp.x, g * D_ + j * 128 + i * 64, m * 64, BAR_ONE(sb, EV_X + g));
        };
        if (elect_one()) {
            if (warp == 8) {
                mbar_init(BAR_ONE(sb, EV_X), 1); mbar_init(BAR_ONE(sb, EV_X1), 1);
                if (!aux) load_x(1);
                if (!HEAD && !aux) load_x(0);
#pragma unroll
                for (int i = 0; i < WP; ++i) {
                    mbar_init(BAR_ONE(sb, EV_WIN + i), 1);
                    if (!aux) {
                        mbar_expect_tx(BAR_ONE(sb, EV_WIN + i), 32768 / WP);
                        tma_load(sb + OFF_OWN + i * (32768 / WP), &mp.wm, (m * 2 + (j >> 2)) * 64, (j & 3) * 256 + i * (256 / WP), BAR_ONE(sb, EV_WIN + i));
                    }
                }
                if (HEAD == 1 && !aux) load_x(0);
                prefetch_map(&mp.ld[aux ? L_WMOD : L_WQKV]);
            } else if (warp < 11) {
#pragma unroll
                for (int i = 0; i < 3; ++i) mbar_init(BAR_FULL(sb, (warp - 9) * 3 + i), aux ? 1 : 2);
#pragma unroll
                for (int i = 0; i < 2; ++i) mbar_init(BAR_SFULL(sb, (warp - 9) * 2 + i), 4);
#pragma unroll
                for (int i = 0; i < 3; ++i) mbar_init(BAR_EMPTY(sb, (warp - 9) * 3 + i), aux ? 2 : 4);
            } else {
#pragma unroll
                for (int i = EV_GA; i < EV_COUNT; ++i) mbar_init(BAR_ONE(sb, i), i == EV_HB ? 8 : i == EV_P2 ? 2 : 1);
            }
            asm volatile("fence.mbarrier_init.release.cluster;" ::: "memory");
        }
        __syncwarp();
        cluster_arrive();
        cluster_wait();
        const bool el = elect_one();
        const int kown = j * 128;
        auto first_tiles = [&](int i0, int i1) {
#pragma unroll 1
            for (int i = i0; i < i1; ++i) {
                if (el && i < 4) mbar_arrive(BAR_FULL(sb, i));
                if (el) {
                    mbar_expect_tx(BAR_FULL(sb, i), 24576);
                    tma_load5_mc(sb + i * SLOT + 8192 + rank * 12288, &mp.ld[L_WQKV], 0, (i < 4 ? kown + i * 32 : j ? 0 : 128) + rank * 16, 2 * j, 0, 0, BAR_FULL(sb, i));
                }
            }
        };
        if (!aux && warp == 8) {
            if (HEAD > 1) { mbar_wait(BAR_ONE(sb, EV_X1 + HEAD - 2), 0); if (el) load_x(0); }
            first_tiles(0, NB0);
        }
        if (sil) {
            const uint32_t s0 = pack2(silu_(bf_lo(cv.x)), silu_(bf_hi(cv.x))), s1 = pack2(silu_(bf_lo(cv.y)), silu_(bf_hi(cv.y))),
                           s2 = pack2(silu_(bf_lo(cv.z)), silu_(bf_hi(cv.z))), s3 = pack2(silu_(bf_lo(cv.w)), silu_(bf_hi(cv.w)));
#pragma unroll
            for (int i = 0; i < 4; ++i) {
                const uint32_t row = aux ? 0 : (warp & 1) * 4 + i;
                sts128(sb + (aux ? OFF_STG + (warp & 3) * 4096 : 4 * SLOT) + (lane >> 3) * 1024 + row * 128 + (((lane & 7) ^ row) << 4), s0, s1, s2, s3);
            }
            fence_async_smem();
        }
        bar_sync(4, 128);
        if (warp == 11) TX(9);
        if (!aux) {
            float acc[32];
#pragma unroll
            for (int i = 0; i < 32; ++i) acc[i] = 0.f;
#pragma unroll 1
            for (int h = 0; h < WP; ++h) {
                mbar_wait(BAR_ONE(sb, EV_WIN + h), 0);
                if (warp == 11) TX(3);
                wg_fence();
#pragma unroll
                for (int k = 0; k < 16 / WP; ++k)
                    wgmma_n64<0>(acc, mk_desc(d16(sb) + h * (256 / WP), 4 * SLOT + (k >> 2) * 1024 + (k & 3) * 32, 16, 0, 1), mk_desc(d16(sb) + h * (2048 / WP), OFF_OWN + k * 2048, 8192, 1024, 1));
                wg_commit();
            }
            ep = __shfl_sync(0xffffffffu, ep, 0) / NCTA + 1;
            wg_wait<0>();
            const uint32_t i = warp & 3;
            auto pick = [&](int e) { return __float_as_uint(i & 2 ? (i & 1 ? acc[24 + e] : acc[16 + e]) : (i & 1 ? acc[8 + e] : acc[e])); };
            st_pkt16(modp, (pick(0) & ~3u) | (1 + (ep & 1)), pick(1), pick(4), pick(5));
            if (warp == 11) TX(4);
        } else if (warp == 8) {
            ep = __shfl_sync(0xffffffffu, ep, 0) / NCTA + 1;
            while (!(ld_pkt16(pt.mail->mod1 + 256).x & (1 + (ep & 1)))) __nanosleep(200);
        }
        asm volatile("setmaxnreg.dec.sync.aligned.u32 %0;" :: "n"(504 - 2 * RC));

        if (warp == 8 || (warp == 11 && !aux)) {
            const bool act = warp == 11;
            if (act) {
                const uint4* pk = pt.mail->mod1 + grp * 2048 + j * 32 + lane;
                uint4 a[8];
                while (true) {
                    uint32_t t = 1 + (ep & 1);
#pragma unroll
                    for (int i = 0; i < 8; ++i) { a[i] = ld_pkt16(pk + i * 256); t &= a[i].x; }
                    if (__all_sync(0xffffffffu, t != 0)) break;
                }
                uint32_t r[4];
#pragma unroll
                for (int v = 0; v < 2; ++v) {
                    auto sum = [&](uint32_t uint4::*f) { return bf_round((__uint_as_float(a[v].*f) + __uint_as_float(a[2 + v].*f)) + (__uint_as_float(a[4 + v].*f) + __uint_as_float(a[6 + v].*f))) + v; };
                    r[2 * v] = pack2(sum(&uint4::x), sum(&uint4::y)); r[2 * v + 1] = pack2(sum(&uint4::z), sum(&uint4::w));
                }
                sts128(sb + OFF_PAR + lane * 16, r[0], r[1], r[2], r[3]);
                __syncwarp();
                if (el) mbar_arrive(BAR_ONE(sb, EV_PAR));
                if (warp == 11) TX(7);
            }
            {
                const uint32_t split = sg.z >> 20, bytes = (sg.z & 63) << 10;
                const uint32_t dst = split ? (split >= 3 ? 16384 : 8192) + rank * (split == 2 ? 4096 : bytes >> 1) : 0;
                const uint32_t blk = ((sg.z >> 8) & 15) * j + ((sg.z >> 12) & 255) + (split == 3 ? rank : 0);
                if (split == 2) sg.x += rank << 24;
                if (split == 1 || split == 4) sg.y |= rank << (12 + (split >> 2));
                sg.z = dst | blk << 16 | (sg.z & 63) << 24;
            }
            if (!act && !aux) { mbar_wait(BAR_ONE(sb, EVB), 0); first_tiles(NB0, 5); }
            Ring r{0, 1};
#pragma unroll 1
            for (int s = 0; ; ++s) {
                const uint32_t x = __shfl_sync(0xffffffffu, sg.x, s), y = __shfl_sync(0xffffffffu, sg.y, s), z = __shfl_sync(0xffffffffu, sg.z, s), w = __shfl_sync(0xffffffffu, sg.w, s);
                const uint32_t nx = __shfl_sync(0xffffffffu, sg.x, s + 1);
                if (!x) break;
                if (el) { prefetch_map(&mp.ld[nx >> 24]); prefetch_map(&mp.ld[(nx >> 24) + 1]); }
                const CUtensorMap* const tm = &mp.ld[x >> 24];
                const uint32_t n = x & 255, blk = (z >> 16) & 255, bytes = (z >> 24) << 10, cnt = w >> 24, base = sb + (z & 0xFFFF);
                if (x & (F_SKIP << 16)) {
                    r.slot += n;
                    if (r.slot >= NSLOT) { r.slot -= NSLOT; r.par ^= 1; }
                    continue;
                }
                uint32_t kl;
                {
                    const uint32_t a = (y >> 2) & 63, step = (y >> 16) & 255, ch = a + lane * (step >> 5), u = ch >> 1, q = u < 7 ? u : u - 7;
                    kl = (y & 3) == K_PANEL ? (q + (q >= j)) * 128 + (u < 7 ? 0 : 64) + (ch & 1) * 32
                                            : ch * 32 + ((lane * ((x >> 8) & 255)) >> 7) * (y >> 24) * 64 + ((y & 3) == K_OWN ? kown : 0);
                    kl += (y >> 8) & 48;
                }
                uint32_t wrap = NSLOT - ((x >> 16) & F_WRAP);
                auto acquire = [&](uint32_t& st, uint32_t& fb) {
                    mbar_wait(BAR_EMPTY(sb, r.slot), r.par);
                    st = base + r.slot * SLOT; fb = BAR_FULL(sb, r.slot);
                    if (++r.slot == wrap) { r.slot = 0; r.par ^= 1; }
                    wrap = NSLOT;
                };
                uint32_t st, fb;
                if (w & 0xFFFF) { mbar_wait(sb + OFF_BAR + (w & 0xFFF8), w & 1); fence_async_global(); }
                if (act | aux) {
                    const uint32_t* const fl = g_flags + m * 64 + cnt * 16 + ((kl >> 6) & 15);
                    const int row = (x >> 24) == L_X ? m * 64 : m * 128;
                    uint32_t ready = cnt ? 0 : ~0u;
                    auto need = [&](uint32_t i, uint32_t bits) {
                        while (!((ready >> i) & 1)) {
                            uint32_t v; asm volatile("ld.relaxed.gpu.global.u32 %0, [%1];" : "=r"(v) : "l"(fl) : "memory");
                            ready = __ballot_sync(0xffffffffu, ((v + 3 - 3 * ep) & bits) == bits);
                            fence_async_global();
                        }
                    };
                    if (x & (F_EARLY << 16)) {
                        const uint32_t k0 = __shfl_sync(0xffffffffu, kl, 0), k2 = __shfl_sync(0xffffffffu, kl, 2);
#pragma unroll
                        for (int e = 0; e < 3; ++e) mbar_wait(BAR_FULL(sb, e), 0);
#pragma unroll 1
                        for (int g = 1; g >= 0; --g) {
                            ready = 0;
#pragma unroll
                            for (int e = 0; e < 4; ++e) {
                                if (!(e & 1)) need(e, 3 - 2 * g);
                                fb = g ? BAR_FULL(sb, e ? e - 1 : 4) : BAR_ONE(sb, EV_A0 + e);
                                if (el) { mbar_expect_tx(fb, 4096); tma_load4(sb + (e ? e - 1 : 4) * SLOT + g * 4096, tm + 1, (e < 2 ? k0 : k2) + (e & 1) * 32, row + g * 64, 0, fb); }
                                if (e == TRIG - 4 && !g && el) mbar_arrive(BAR_ONE(sb, EV_SEC));
                            }
                        }
                        r.slot = 3; r.par ^= 1;
                    }
#pragma unroll 1
                    for (uint32_t i = (x >> 17) & 4; i < n; ++i) {
                        const uint32_t k = __shfl_sync(0xffffffffu, kl, i);
                        need(i, 3);
                        acquire(st, fb);
                        if (el) { mbar_expect_tx(fb, bytes); tma_load4(st, tm, aux ? 0 : k, aux ? k : row, aux ? blk : 0, fb); }
                    }
                } else {
                    const bool twice = el && (x & (F_TWICE << 16)), wd = (x >> 24) == L_WD;
                    const uint32_t more = (x >> 25) == L_WG / 2 ? (bytes >> 13) - 1 : 0;
#pragma unroll 1
                    for (uint32_t i = 0; i < n; ++i) {
                        const uint32_t k = __shfl_sync(0xffffffffu, kl, i);
                        acquire(st, fb);
                        if (twice) mbar_arrive(fb);
                        if (el) { mbar_expect_tx(fb, bytes); tma_load5_mc(st, tm, wd ? blk * 64 : 0, wd ? 0 : k, wd ? 0 : blk, (x >> 24) == L_WKV, wd ? k >> 5 : 0, fb); }
                        if (more && el) tma_load5_mc(st + 8192, tm, 0, k, blk + 1, 0, 0, fb);
                        if (more > 1 && el) tma_load5_mc(st + 16384, tm, 0, k, blk + 2, 0, 0, fb);
                    }
                }
            }
        } else if (!aux) {
            const uint32_t w = warp - 9;
            uint32_t bpar = 0;
            auto send = [&](int t) {
                const CUtensorMap* const tm = t ? &mp.os : &mp.h1s;
                const bool ring = t != 1;
                const uint32_t src = sb + (ring ? OFF_OWN : OFF_STG), par = t & 1;
#pragma unroll 1
                for (uint32_t u = w ? 0 : 1; u < (w ? 1 : 3); ++u) {
                    const uint32_t p = u >> 1, g1 = !(ring && u == 1), g0 = u == 0;
                    if (p && ring) mbar_wait_b(BAR_ONE(sb, EV_SEC), t >> 1);
                    const int col = kown + p * 64, row = m * 128 + g0 * 64;
                    const uint32_t back = BAR_ONE(sb, EV_BACK + w), from = src + p * 16384;
                    if (g1 != g0) {
                        mbar_wait_b(BAR_SFULL(sb, 2 + p), par);
                        if (el) { fence_async_smem(); tma_store(tm, col, row + 64, from + 8192); }
                    }
                    mbar_wait_b(BAR_SFULL(sb, 2 * g0 + p), par);
                    if (el) {
                        fence_async_smem();
                        tma_store(tm, col, row, from + g0 * 8192);
                        bulk_commit();
                        mbar_expect_tx(back, 2048);
                        bulk_wait_all();
#pragma unroll
                        for (int i = 0; i < 4; ++i) tma_load(sb + OFF_JUNK, tm + 2, col, row + (i & 1) * 32 + (i >> 1) * (g1 - g0) * 64, back);
                    }
                    __syncwarp();
                    if (p && ring) {
                        mbar_wait_b(BAR_FULL(sb, 5), 0); mbar_wait_b(BAR_ONE(sb, EV_BACK + 1), t >> 1);
                        if (lane < 4) asm volatile("{\n.reg .b32 r;\nmapa.shared::cluster.u32 r, %0, %1;\nmbarrier.arrive.shared::cluster.b64 _, [r];\n}" :: "r"(BAR_EMPTY(sb, 5)), "r"(lane & 1) : "memory");
                    }
                    mbar_wait_b(back, bpar);
                    bpar ^= 1;
                    if (el) asm volatile("red.relaxed.gpu.global.add.u32 [%0], %1;" :: "l"(g_flags + m * 64 + 16 + t * 16 + 2 * j + p), "r"(g1 + 2 - 2 * g0) : "memory");
                    TX(10 + t * 4 + u);
                    if (el && u == 1) TS(43 + t);
                }
            };
            auto gate = [&](int vec, int ev) {
                uint2 a, b; uint32_t n = 0;
                const uint2* src = g_mod + vec * 512 + j * 64 + (lane >> 2) * 8 + (lane & 3);
                while (true) {
                    a = ld_pkt(src); b = ld_pkt(src + 4);
                    if (__all_sync(0xffffffffu, a.y == ep && b.y == ep)) break;
                    SPIN_GUARD(n); __nanosleep(300);
                }
                sts128(sb + OFF_TAB + (ev - EV_GA) * 512 + lane * 16, a.x << 16, a.x & 0xFFFF0000u, b.x << 16, b.x & 0xFFFF0000u);
                __syncwarp();
                if (el) mbar_arrive(BAR_ONE(sb, ev));
            };
            if (lane < 6) prefetch_map(lane < 4 ? &mp.h1s + lane : &mp.ld[L_H1 - 4 + lane]);
            auto count = [&](int f) {
                uint32_t v, n = 0;
                while (true) {
                    asm volatile("ld.acquire.gpu.global.u32 %0, [%1];" : "=r"(v) : "l"(g_flags + f) : "memory");
                    if ((int32_t)(v - ep * 8) >= 0) break;
                    SPIN_GUARD(n); __nanosleep(500);
                }
            };
#pragma unroll 1
            for (int t = 0; t < 3; t += 1 + w) {
                send(t);
                if (w == 0) {
                    if (t && el) mbar_arrive(BAR_ONE(sb, t == 1 ? EV_P2 : EV_SENT));
                    if (t == 1 && m > 0) {
#pragma unroll 4
                        for (int i = 0; i < 16; ++i) (g_halo + ((m - 1) * 8 + j) * 512 + lane)[i * 32] = make_uint4(0, 0, 0, 0);
                    }
                } else {
                    gate(t ? 5 : 2, t ? EV_GB : EV_GA);
                    if (t == 0) {
                        count(FL_LN2);
                        const uint4 v = __ldcg((const uint4*)(g_par2 + j * 128) + lane);
                        mbar_wait_b(BAR_SFULL(sb, 2), 1);
                        sts128(sb + OFF_PAR + lane * 16, v.x, v.y, v.z, v.w);
                        __syncwarp();
                        if (el) mbar_arrive(BAR_ONE(sb, EV_P2));
                    }
                }
            }
            if (w) {
#pragma unroll 1
                for (int p = 0; p < 3; ++p) {
                    mbar_wait_b(BAR_ONE(sb, EV_HB), p & 1);
                    __nanosleep(RESTH);
                    if (el) asm volatile("red.release.gpu.global.add.u32 [%0], 1;" :: "l"(g_flags + m * 64 + p) : "memory");
                    count(m * 64 + p);
                    if (el) mbar_arrive(BAR_ONE(sb, EV_H + p));
                }
            }
            cluster_arrive_early = true;
            cluster_arrive();
            mbar_wait_b(BAR_SFULL(sb, w * 2), 1);
        }
        __syncwarp();
    }
    if (aux || (wg == 2 && !cluster_arrive_early)) cluster_arrive();
    cluster_wait();
    if (tid == 0) {
        flag_add(pt.mail->flags + FL_DONE);
    }
}

typedef CUresult (*EncodeFn)(CUtensorMap*, CUtensorMapDataType, cuuint32_t, void*, const cuuint64_t*, const cuuint64_t*, const cuuint32_t*,
                             const cuuint32_t*, CUtensorMapInterleave, CUtensorMapSwizzle, CUtensorMapL2promotion, CUtensorMapFloatOOBfill);

void make_map(EncodeFn fn, CUtensorMap* m, const void* ptr, uint64_t rows, uint64_t cols, uint32_t brows, uint32_t bcols) {
    cuuint64_t dims[2] = {cols, rows}, strides[1] = {cols * 2};
    cuuint32_t box[2] = {bcols, brows}, es[2] = {1, 1};
    fn(m, CU_TENSOR_MAP_DATA_TYPE_BFLOAT16, 2, (void*)ptr, dims, strides, box, es, CU_TENSOR_MAP_INTERLEAVE_NONE,
       bcols == 64 ? CU_TENSOR_MAP_SWIZZLE_128B : bcols == 32 ? CU_TENSOR_MAP_SWIZZLE_64B : CU_TENSOR_MAP_SWIZZLE_NONE, CU_TENSOR_MAP_L2_PROMOTION_L2_256B, CU_TENSOR_MAP_FLOAT_OOB_FILL_NONE);
}
struct View { uint64_t dim[5], stride[4]; uint32_t box[5]; };
void make_view(EncodeFn fn, CUtensorMap* m, const void* ptr, uint32_t rank, const View& v) {
    cuuint64_t dims[5], strides[4];
    cuuint32_t box[5], es[5] = {1, 1, 1, 1, 1};
    for (int i = 0; i < 5; ++i) { dims[i] = v.dim[i]; box[i] = v.box[i]; if (i < 4) strides[i] = v.stride[i] * 2; }
    fn(m, CU_TENSOR_MAP_DATA_TYPE_BFLOAT16, rank, (void*)ptr, dims, strides, box, es, CU_TENSOR_MAP_INTERLEAVE_NONE,
       box[0] == 64 ? CU_TENSOR_MAP_SWIZZLE_128B : CU_TENSOR_MAP_SWIZZLE_64B, CU_TENSOR_MAP_L2_PROMOTION_L2_256B, CU_TENSOR_MAP_FLOAT_OOB_FILL_NONE);
}

}

extern "C" void kernel_launch(void* const* d_in, const int* in_sizes, int n_in, void* d_out, int out_size) {
    (void)in_sizes; (void)n_in; (void)out_size;
    void* fnp = nullptr;
    cudaDriverEntryPointQueryResult qr;
    cudaGetDriverEntryPoint("cuTensorMapEncodeTiled", &fnp, cudaEnableDefault, &qr);
    EncodeFn fn = (EncodeFn)fnp;
    void *h1, *o, *hb, *mail, *sched;
    cudaGetSymbolAddress(&h1, g_h1);
    cudaGetSymbolAddress(&mail, g_mail);
    cudaGetSymbolAddress(&o, g_o);
    cudaGetSymbolAddress(&hb, g_hb);
    cudaGetSymbolAddress(&sched, g_sched);
    Maps mp;
    auto wmap = [&](int i, const void* p, uint64_t rows, uint64_t cols, uint64_t sec, uint32_t brows, uint32_t bblk, uint32_t bsec) {
        make_view(fn, &mp.ld[i], p, i == L_WMOD ? 4 : 5, View{{64, rows, cols / sec / 64, sec, 1}, {cols, 64, cols / sec, 64}, {64, brows, bblk, bsec, 1}});
    };
    auto amap = [&](int i, const void* p, uint64_t cols, uint32_t bcols, uint32_t brows = 128) { make_view(fn, &mp.ld[i], p, 4, View{{cols, S_, 1, 1, 1}, {cols, 64, 64, 64}, {bcols, brows, 1, 1, 1}}); };
    wmap(L_WQKV, d_in[1], D_, 3 * D_, 3, 16, 2, 3);
    wmap(L_WKV, d_in[1], D_, 3 * D_, 3, 16, 2, 2);
    wmap(L_WQ, d_in[1], D_, 3 * D_, 3, 64, 1, 1);
    wmap(L_WQ1, d_in[1], D_, 3 * D_, 3, 32, 1, 1);
    wmap(L_WO, d_in[2], D_, D_, 1, 64, 1, 1);
    wmap(L_WG, d_in[4], D_, F_, 1, 32, 1, 1);
    wmap(L_WU, d_in[5], D_, F_, 1, 32, 1, 1);
    make_view(fn, &mp.ld[L_WD], d_in[6], 5, View{{D_, 2, 4, 4, F_ / 32}, {D_, 8 * D_, 2 * D_, 32 * D_}, {64, 2, 4, 4, 2}});
    wmap(L_WMOD, d_in[8], D_, 6 * D_, 1, 64, 4, 1);
    amap(L_H1, h1, D_, 32); amap(L_H1Q, h1, D_, 64); amap(L_O, o, D_, 64); amap(L_H2, o, D_, 32); amap(L_HB, hb, F_, 64);
    amap(L_H1E, h1, D_, 32, 64); amap(L_H2E, o, D_, 32, 64);
    make_view(fn, &mp.ld[L_X], d_in[0], 4, View{{D_, S_ / 2, 2, 1, 1}, {2 * D_, D_, 64, 64}, {64, 64, 2, 1, 1}});
    make_map(fn, &mp.h1s, h1, S_, D_, 64, 64);
    make_map(fn, &mp.os, o, S_, D_, 64, 64);
    make_map(fn, &mp.h1r, h1, S_, D_, 32, 8);
    make_map(fn, &mp.orr, o, S_, D_, 32, 8);
    make_map(fn, &mp.wm, d_in[8], D_, 6 * D_, 256 / WP, 64);
    make_map(fn, &mp.x, d_in[0], S_ / 2, 2 * D_, 64, 64);
    make_map(fn, &mp.out, d_out, S_ / 2, 2 * D_, 16, 64);
    cudaFuncSetAttribute(fused_block_kernel, cudaFuncAttributeMaxDynamicSharedMemorySize, SMEM_BYTES);
    cudaLaunchConfig_t cfg = {};
    cfg.gridDim = dim3(NCTA); cfg.blockDim = dim3(384); cfg.dynamicSmemBytes = SMEM_BYTES; cfg.stream = cudaStreamPerThread;
    cudaLaunchAttribute at[1];
    at[0].id = cudaLaunchAttributeClusterDimension; at[0].val.clusterDim.x = 2; at[0].val.clusterDim.y = 1; at[0].val.clusterDim.z = 1;
    cfg.attrs = at; cfg.numAttrs = 1;
    const Ptrs pt{(const __nv_bfloat16*)d_in[7], (Mail*)mail, (__nv_bfloat16*)hb, (const uint4*)sched};
    cudaLaunchKernelEx(&cfg, fused_block_kernel, pt, mp);
}
```

```cpp
#include <cuda_runtime.h>
#include <cuda_bf16.h>
#include <cuda.h>
#include <stdint.h>
#include <stddef.h>

constexpr int LAG = 3;
constexpr int LAGS = 2;
constexpr int LAGW = 4;
constexpr int LAGD = 3;
constexpr int LAGQ = 3;
constexpr int EARLY = 1;
constexpr int NQ = 6;
constexpr int NS = 5;
constexpr int RC = 224;
constexpr int RESTH = 1000;
constexpr int NB0 = 2;
constexpr int GW = 4;
constexpr int GD = 2;
constexpr int SWO = 2;
constexpr int NB1 = 3;
constexpr int QA = 3;

namespace {

constexpr int S_ = 2048, D_ = 1024, F_ = 3584;
constexpr int NCTA = 132;
constexpr int NSLOT = 6;
constexpr uint32_t SLOT = 32768;
constexpr uint32_t OFF_STG = NSLOT * SLOT;
constexpr uint32_t OFF_BAR = OFF_STG + 32768;
constexpr uint32_t OFF_PAR = OFF_BAR + 384;
constexpr uint32_t OFF_TAB = OFF_PAR + 512;
constexpr uint32_t OFF_JUNK = 0u - 1024;
constexpr uint32_t SMEM_BYTES = 1024 + OFF_TAB + 1024;
constexpr int ST_Q = 33, ST_WO = ST_Q + NQ + NS, ST_GU = ST_WO + 16, ST_G1 = ST_GU + 33;
static_assert(ST_GU % (2 * NSLOT) == 0, "");
constexpr uint32_t OFF_OWN = 5 * SLOT;
constexpr uint32_t sweep_order() {
    uint32_t v = 0, n = 0;
    for (uint32_t hi = 0; hi < 2; ++hi)
        for (int i = 0; i < NS; ++i) { const uint32_t t = ST_WO - NS + i, s = t % NSLOT; if ((s >= 4) == hi) v |= (s | (t / NSLOT & 1) << 3) << (4 * n++); }
    return v;
}
constexpr uint32_t SWEEP = sweep_order();

constexpr int FL_DONE = 16 * 64, FL_LN2 = 16 * 64 + 1;

enum { L_WQKV, L_WKV, L_WQ, L_WO, L_WG, L_WU, L_WQ1, L_WD, L_WMOD, L_H1, L_H1E, L_H1Q, L_X, L_O, L_H2, L_H2E, L_HB, L_COUNT };
struct Maps {
    CUtensorMap wm, x, h1s, os, h1r, orr, ld[L_COUNT], out;
};

struct Mail {
    uint32_t flags[16 * 64 + 32];
    uint2 mod[6 * D_ / 2];
    uint4 mod1[8 * 2048];
    uint4 st1[8 * S_ / 2];
    uint32_t par2[D_];
    uint4 halo[128 * 512];
};
struct Ptrs { const __nv_bfloat16* c; Mail* mail; __nv_bfloat16* hb; const uint4* sched; };

__device__ __align__(128) Mail g_mail;
__device__ __align__(128) __nv_bfloat16 g_h1[S_ * D_];
__device__ __align__(128) __nv_bfloat16 g_o[S_ * D_];
__device__ __align__(128) __nv_bfloat16 g_hb[S_ * F_];

__device__ __forceinline__ uint32_t smem_u32(const void* p) { return (uint32_t)__cvta_generic_to_shared(p); }
__device__ __forceinline__ void mbar_init(uint32_t bar, uint32_t cnt) { asm volatile("mbarrier.init.shared::cta.b64 [%0], %1;" :: "r"(bar), "r"(cnt) : "memory"); }
__device__ __forceinline__ void mbar_expect_tx(uint32_t bar, uint32_t bytes) { asm volatile("mbarrier.arrive.expect_tx.shared::cta.b64 _, [%0], %1;" :: "r"(bar), "r"(bytes) : "memory"); }
__device__ __forceinline__ void mbar_arrive(uint32_t bar) { asm volatile("mbarrier.arrive.shared::cta.b64 _, [%0];" :: "r"(bar) : "memory"); }
__device__ __forceinline__ void mbar_arrive_if0(uint32_t bar, uint32_t z) {
    asm volatile("{\n.reg .pred p;\nsetp.eq.u32 p, %1, 0;\n@p mbarrier.arrive.shared::cta.b64 _, [%0];\n}" :: "r"(bar), "r"(z) : "memory");
}
__device__ __forceinline__ void mbar_wait(uint32_t bar, uint32_t parity) {
    asm volatile("{\n.reg .pred p;\nW_LOOP:\nmbarrier.try_wait.parity.shared::cta.b64 p, [%0], %1;\n@!p bra W_LOOP;\n}" :: "r"(bar), "r"(parity) : "memory");
}
__device__ __forceinline__ void mbar_wait_b(uint32_t bar, uint32_t parity) {
    asm volatile("{\n.reg .pred p;\n.reg .u32 n;\nmov.u32 n, 0;\n"
        "W_LOOP:\nmbarrier.try_wait.parity.shared::cta.b64 p, [%0], %1;\n@p bra W_DONE;\n"
        "add.u32 n, n, 1;\nsetp.lt.u32 p, n, 0x400000;\n@p bra W_LOOP;\ntrap;\nW_DONE:\n}" :: "r"(bar), "r"(parity) : "memory");
}
__device__ __forceinline__ void tma_load(uint32_t dst, const CUtensorMap* m, int c0, int c1, uint32_t bar) {
    asm volatile("cp.async.bulk.tensor.2d.shared::cluster.global.mbarrier::complete_tx::bytes [%0], [%1, {%3, %4}], [%2];"
        :: "r"(dst), "l"(m), "r"(bar), "r"(c0), "r"(c1) : "memory");
}
__device__ __forceinline__ void tma_load4(uint32_t dst, const CUtensorMap* m, int c0, int c1, int c2, uint32_t bar) {
    asm volatile("cp.async.bulk.tensor.4d.shared::cluster.global.mbarrier::complete_tx::bytes [%0], [%1, {%3, %4, %5, %6}], [%2];"
        :: "r"(dst), "l"(m), "r"(bar), "r"(c0), "r"(c1), "r"(c2), "r"(0) : "memory");
}
__device__ __forceinline__ void tma_load5_mc(uint32_t dst, const CUtensorMap* m, int c0, int c1, int c2, int c3, int c4, uint32_t bar) {
    asm volatile("cp.async.bulk.tensor.5d.shared::cluster.global.mbarrier::complete_tx::bytes.multicast::cluster.L2::cache_hint [%0], [%1, {%3, %4, %5, %6, %7}], [%2], %8, %9;"
        :: "r"(dst), "l"(m), "r"(bar), "r"(c0), "r"(c1), "r"(c2), "r"(c3), "r"(c4), "h"((uint16_t)3), "l"(0x12F0000000000000ull) : "memory");
}
__device__ __forceinline__ void tma_store(const CUtensorMap* m, int c0, int c1, uint32_t src) {
    asm volatile("cp.async.bulk.tensor.2d.global.shared::cta.bulk_group [%0, {%2, %3}], [%1];" :: "l"(m), "r"(src), "r"(c0), "r"(c1) : "memory");
}
__device__ __forceinline__ void bulk_commit() { asm volatile("cp.async.bulk.commit_group;" ::: "memory"); }
__device__ __forceinline__ void bulk_wait_read() { asm volatile("cp.async.bulk.wait_group.read 0;" ::: "memory"); }
__device__ __forceinline__ void bulk_wait_all() { asm volatile("cp.async.bulk.wait_group 0;" ::: "memory"); }
__device__ __forceinline__ void fence_async_smem() { asm volatile("fence.proxy.async.shared::cta;" ::: "memory"); }
__device__ __forceinline__ void fence_async_global() { asm volatile("fence.proxy.async.global;" ::: "memory"); }
__device__ __forceinline__ void prefetch_map(const CUtensorMap* m) { asm volatile("prefetch.tensormap [%0];" :: "l"(m) : "memory"); }
__device__ __forceinline__ void wg_fence() { asm volatile("wgmma.fence.sync.aligned;" ::: "memory"); }
__device__ __forceinline__ void wg_commit() { asm volatile("wgmma.commit_group.sync.aligned;" ::: "memory"); }
template <int N> __device__ __forceinline__ void wg_wait() { asm volatile("wgmma.wait_group.sync.aligned %0;" :: "n"(N) : "memory"); }
__device__ __forceinline__ void bar_sync(int id, int n) { asm volatile("bar.sync %0, %1;" :: "r"(id), "r"(n) : "memory"); }
__device__ __forceinline__ void flag_add(uint32_t* f) { asm volatile("red.relaxed.gpu.global.add.u32 [%0], 1;" :: "l"(f) : "memory"); }
__device__ __forceinline__ uint32_t d16(uint32_t addr) { return (addr & 0x3FFFF) >> 4; }
__device__ __forceinline__ uint64_t mk_desc(uint32_t a16, uint32_t off, uint32_t lbo, uint32_t sbo, uint32_t swz) {
    const uint32_t lo = a16 + (off >> 4) + ((lbo >> 4) << 16), hi = (sbo >> 4) | (swz << 30);
    return ((uint64_t)hi << 32) | lo;
}
__device__ __forceinline__ uint32_t pack2(float lo, float hi) {
    uint32_t r; asm("cvt.rn.bf16x2.f32 %0, %1, %2;" : "=r"(r) : "f"(hi), "f"(lo)); return r;
}
__device__ __forceinline__ uint32_t hfma2_bf16(uint32_t a, uint32_t b, uint32_t c) {
    uint32_t r; asm("fma.rn.bf16x2 %0, %1, %2, %3;" : "=r"(r) : "r"(a), "r"(b), "r"(c)); return r;
}
__device__ __forceinline__ float bf_lo(uint32_t v) { return __uint_as_float(v << 16); }
__device__ __forceinline__ float bf_hi(uint32_t v) { return __uint_as_float(v & 0xFFFF0000u); }
__device__ __forceinline__ float bf_round(float x) { return __bfloat162float(__float2bfloat16_rn(x)); }
__device__ __forceinline__ void stsm4(uint32_t addr, uint32_t r0, uint32_t r1, uint32_t r2, uint32_t r3) {
    asm volatile("stmatrix.sync.aligned.m8n8.x4.shared.b16 [%0], {%1, %2, %3, %4};" :: "r"(addr), "r"(r0), "r"(r1), "r"(r2), "r"(r3) : "memory");
}
__device__ __forceinline__ void stsm4t(uint32_t addr, uint32_t r0, uint32_t r1, uint32_t r2, uint32_t r3) {
    asm volatile("stmatrix.sync.aligned.m8n8.x4.trans.shared.b16 [%0], {%1, %2, %3, %4};" :: "r"(addr), "r"(r0), "r"(r1), "r"(r2), "r"(r3) : "memory");
}
__device__ __forceinline__ void ldsm4(uint32_t addr, uint32_t& r0, uint32_t& r1, uint32_t& r2, uint32_t& r3) {
    asm volatile("ldmatrix.sync.aligned.m8n8.x4.shared.b16 {%0, %1, %2, %3}, [%4];" : "=r"(r0), "=r"(r1), "=r"(r2), "=r"(r3) : "r"(addr) : "memory");
}
__device__ __forceinline__ uint32_t movm(uint32_t a) { uint32_t r; asm volatile("movmatrix.sync.aligned.m8n8.trans.b16 %0, %1;" : "=r"(r) : "r"(a)); return r; }
__device__ __forceinline__ void mma16816(float (&c)[4], uint32_t a0, uint32_t a1, uint32_t a2, uint32_t a3, uint32_t b0, uint32_t b1) {
    asm("mma.sync.aligned.m16n8k16.row.col.f32.bf16.bf16.f32 {%0, %1, %2, %3}, {%4, %5, %6, %7}, {%8, %9}, {%0, %1, %2, %3};"
        : "+f"(c[0]), "+f"(c[1]), "+f"(c[2]), "+f"(c[3]) : "r"(a0), "r"(a1), "r"(a2), "r"(a3), "r"(b0), "r"(b1));
}
__device__ __forceinline__ float ex2(float x) { float r; asm("ex2.approx.ftz.f32 %0, %1;" : "=f"(r) : "f"(x)); return r; }
__device__ __forceinline__ float rcp(float x) { float r; asm("rcp.approx.ftz.f32 %0, %1;" : "=f"(r) : "f"(x)); return r; }
__device__ __forceinline__ float rsq(float x) { float r; asm("rsqrt.approx.ftz.f32 %0, %1;" : "=f"(r) : "f"(x)); return r; }
__device__ __forceinline__ float silu_(float x) { return x * rcp(1.f + ex2(-1.4426950408889634f * x)); }
__device__ __forceinline__ void st_pkt(void* p, uint32_t a, uint32_t b) {
    asm volatile("{\n.reg .b64 t;\nmov.b64 t, {%1, %2};\nst.relaxed.gpu.global.b64 [%0], t;\n}" :: "l"(p), "r"(a), "r"(b) : "memory");
}
__device__ __forceinline__ uint2 ld_pkt(const void* p) {
    uint2 v; asm volatile("{\n.reg .b64 t;\nld.relaxed.gpu.global.b64 t, [%2];\nmov.b64 {%0, %1}, t;\n}" : "=r"(v.x), "=r"(v.y) : "l"(p) : "memory"); return v;
}
__device__ __forceinline__ void st_pkt16(void* p, uint32_t a, uint32_t b, uint32_t c, uint32_t d) {
    asm volatile("{\n.reg .b64 t, u;\n.reg .b128 w;\nmov.b64 t, {%1, %2};\nmov.b64 u, {%3, %4};\nmov.b128 w, {t, u};\nst.relaxed.gpu.global.b128 [%0], w;\n}"
        :: "l"(p), "r"(a), "r"(b), "r"(c), "r"(d) : "memory");
}
__device__ __forceinline__ uint4 ld_pkt16(const void* p) {
    uint4 v; asm volatile("{\n.reg .b64 t, u;\n.reg .b128 w;\nld.relaxed.gpu.global.b128 w, [%4];\nmov.b128 {t, u}, w;\nmov.b64 {%0, %1}, t;\nmov.b64 {%2, %3}, u;\n}"
        : "=r"(v.x), "=r"(v.y), "=r"(v.z), "=r"(v.w) : "l"(p) : "memory"); return v;
}
#define SPIN_GUARD(n) do { if (++(n) > (1u << 22)) asm volatile("trap;"); } while (0)
__device__ __forceinline__ uint4 lds128(uint32_t a) { uint4 v; asm volatile("ld.shared.v4.u32 {%0, %1, %2, %3}, [%4];" : "=r"(v.x), "=r"(v.y), "=r"(v.z), "=r"(v.w) : "r"(a) : "memory"); return v; }
__device__ __forceinline__ void sts128(uint32_t a, uint32_t x, uint32_t y, uint32_t z, uint32_t w) { asm volatile("st.shared.v4.u32 [%0], {%1, %2, %3, %4};" :: "r"(a), "r"(x), "r"(y), "r"(z), "r"(w) : "memory"); }
__device__ __forceinline__ uint2 lds64(uint32_t a) { uint2 v; asm volatile("ld.shared.v2.u32 {%0, %1}, [%2];" : "=r"(v.x), "=r"(v.y) : "r"(a) : "memory"); return v; }
__device__ __forceinline__ void sts64(uint32_t a, uint32_t x, uint32_t y) { asm volatile("st.shared.v2.u32 [%0], {%1, %2};" :: "r"(a), "r"(x), "r"(y) : "memory"); }
__device__ __forceinline__ uint32_t lds32(uint32_t a) { uint32_t v; asm volatile("ld.shared.u32 %0, [%1];" : "=r"(v) : "r"(a) : "memory"); return v; }
__device__ __forceinline__ void sts32(uint32_t a, uint32_t v) { asm volatile("st.shared.u32 [%0], %1;" :: "r"(a), "r"(v) : "memory"); }
__device__ __forceinline__ bool elect_one() {
    uint32_t p; asm volatile("{\n.reg .pred q;\nelect.sync _|q, 0xffffffff;\nselp.u32 %0, 1, 0, q;\n}" : "=r"(p)); return p;
}
__device__ __forceinline__ void cluster_arrive() { asm volatile("barrier.cluster.arrive.relaxed.aligned;" ::: "memory"); }
__device__ __forceinline__ void cluster_wait() { asm volatile("barrier.cluster.wait.aligned;" ::: "memory"); }

__device__ __forceinline__ void wgmma_n128_z(float (&d)[64], uint64_t da, uint64_t db) {
    asm volatile("{\n.reg .pred p;\nsetp.ne.b32 p, 0, 0;\n"
        "wgmma.mma_async.sync.aligned.m64n128k16.f32.bf16.bf16 {"
        "%0, %1, %2, %3, %4, %5, %6, %7, %8, %9, %10, %11, %12, %13, %14, %15, "
        "%16, %17, %18, %19, %20, %21, %22, %23, %24, %25, %26, %27, %28, %29, %30, %31, "
        "%32, %33, %34, %35, %36, %37, %38, %39, %40, %41, %42, %43, %44, %45, %46, %47, "
        "%48, %49, %50, %51, %52, %53, %54, %55, %56, %57, %58, %59, %60, %61, %62, %63"
        "}, %64, %65, p, 1, 1, 0, 1;\n}\n"
        : "=f"(d[0]), "=f"(d[1]), "=f"(d[2]), "=f"(d[3]), "=f"(d[4]), "=f"(d[5]), "=f"(d[6]), "=f"(d[7]),
          "=f"(d[8]), "=f"(d[9]), "=f"(d[10]), "=f"(d[11]), "=f"(d[12]), "=f"(d[13]), "=f"(d[14]), "=f"(d[15]),
          "=f"(d[16]), "=f"(d[17]), "=f"(d[18]), "=f"(d[19]), "=f"(d[20]), "=f"(d[21]), "=f"(d[22]), "=f"(d[23]),
          "=f"(d[24]), "=f"(d[25]), "=f"(d[26]), "=f"(d[27]), "=f"(d[28]), "=f"(d[29]), "=f"(d[30]), "=f"(d[31]),
          "=f"(d[32]), "=f"(d[33]), "=f"(d[34]), "=f"(d[35]), "=f"(d[36]), "=f"(d[37]), "=f"(d[38]), "=f"(d[39]),
          "=f"(d[40]), "=f"(d[41]), "=f"(d[42]), "=f"(d[43]), "=f"(d[44]), "=f"(d[45]), "=f"(d[46]), "=f"(d[47]),
          "=f"(d[48]), "=f"(d[49]), "=f"(d[50]), "=f"(d[51]), "=f"(d[52]), "=f"(d[53]), "=f"(d[54]), "=f"(d[55]),
          "=f"(d[56]), "=f"(d[57]), "=f"(d[58]), "=f"(d[59]), "=f"(d[60]), "=f"(d[61]), "=f"(d[62]), "=f"(d[63])
        : "l"(da), "l"(db));
}
__device__ __forceinline__ void wgmma_n128(float (&d)[64], uint64_t da, uint64_t db) {
    asm volatile("{\n.reg .pred p;\nsetp.eq.b32 p, 0, 0;\n"
        "wgmma.mma_async.sync.aligned.m64n128k16.f32.bf16.bf16 {"
        "%0, %1, %2, %3, %4, %5, %6, %7, %8, %9, %10, %11, %12, %13, %14, %15, "
        "%16, %17, %18, %19, %20, %21, %22, %23, %24, %25, %26, %27, %28, %29, %30, %31, "
        "%32, %33, %34, %35, %36, %37, %38, %39, %40, %41, %42, %43, %44, %45, %46, %47, "
        "%48, %49, %50, %51, %52, %53, %54, %55, %56, %57, %58, %59, %60, %61, %62, %63"
        "}, %64, %65, p, 1, 1, 0, 1;\n}\n"
        : "+f"(d[0]), "+f"(d[1]), "+f"(d[2]), "+f"(d[3]), "+f"(d[4]), "+f"(d[5]), "+f"(d[6]), "+f"(d[7]),
          "+f"(d[8]), "+f"(d[9]), "+f"(d[10]), "+f"(d[11]), "+f"(d[12]), "+f"(d[13]), "+f"(d[14]), "+f"(d[15]),
          "+f"(d[16]), "+f"(d[17]), "+f"(d[18]), "+f"(d[19]), "+f"(d[20]), "+f"(d[21]), "+f"(d[22]), "+f"(d[23]),
          "+f"(d[24]), "+f"(d[25]), "+f"(d[26]), "+f"(d[27]), "+f"(d[28]), "+f"(d[29]), "+f"(d[30]), "+f"(d[31]),
          "+f"(d[32]), "+f"(d[33]), "+f"(d[34]), "+f"(d[35]), "+f"(d[36]), "+f"(d[37]), "+f"(d[38]), "+f"(d[39]),
          "+f"(d[40]), "+f"(d[41]), "+f"(d[42]), "+f"(d[43]), "+f"(d[44]), "+f"(d[45]), "+f"(d[46]), "+f"(d[47]),
          "+f"(d[48]), "+f"(d[49]), "+f"(d[50]), "+f"(d[51]), "+f"(d[52]), "+f"(d[53]), "+f"(d[54]), "+f"(d[55]),
          "+f"(d[56]), "+f"(d[57]), "+f"(d[58]), "+f"(d[59]), "+f"(d[60]), "+f"(d[61]), "+f"(d[62]), "+f"(d[63])
        : "l"(da), "l"(db));
}
__device__ __forceinline__ void wgmma_n256_z(float (&d)[128], uint64_t da, uint64_t db) {
    asm volatile("{\n.reg .pred p;\nsetp.ne.b32 p, 0, 0;\n"
        "wgmma.mma_async.sync.aligned.m64n256k16.f32.bf16.bf16 {"
        "%0, %1, %2, %3, %4, %5, %6, %7, %8, %9, %10, %11, %12, %13, %14, %15, "
        "%16, %17, %18, %19, %20, %21, %22, %23, %24, %25, %26, %27, %28, %29, %30, %31, "
        "%32, %33, %34, %35, %36, %37, %38, %39, %40, %41, %42, %43, %44, %45, %46, %47, "
        "%48, %49, %50, %51, %52, %53, %54, %55, %56, %57, %58, %59, %60, %61, %62, %63, "
        "%64, %65, %66, %67, %68, %69, %70, %71, %72, %73, %74, %75, %76, %77, %78, %79, "
        "%80, %81, %82, %83, %84, %85, %86, %87, %88, %89, %90, %91, %92, %93, %94, %95, "
        "%96, %97, %98, %99, %100, %101, %102, %103, %104, %105, %106, %107, %108, %109, %110, %111, "
        "%112, %113, %114, %115, %116, %117, %118, %119, %120, %121, %122, %123, %124, %125, %126, %127"
        "}, %128, %129, p, 1, 1, 0, 1;\n}\n"
        : "=f"(d[0]), "=f"(d[1]), "=f"(d[2]), "=f"(d[3]), "=f"(d[4]), "=f"(d[5]), "=f"(d[6]), "=f"(d[7]),
          "=f"(d[8]), "=f"(d[9]), "=f"(d[10]), "=f"(d[11]), "=f"(d[12]), "=f"(d[13]), "=f"(d[14]), "=f"(d[15]),
          "=f"(d[16]), "=f"(d[17]), "=f"(d[18]), "=f"(d[19]), "=f"(d[20]), "=f"(d[21]), "=f"(d[22]), "=f"(d[23]),
          "=f"(d[24]), "=f"(d[25]), "=f"(d[26]), "=f"(d[27]), "=f"(d[28]), "=f"(d[29]), "=f"(d[30]), "=f"(d[31]),
          "=f"(d[32]), "=f"(d[33]), "=f"(d[34]), "=f"(d[35]), "=f"(d[36]), "=f"(d[37]), "=f"(d[38]), "=f"(d[39]),
          "=f"(d[40]), "=f"(d[41]), "=f"(d[42]), "=f"(d[43]), "=f"(d[44]), "=f"(d[45]), "=f"(d[46]), "=f"(d[47]),
          "=f"(d[48]), "=f"(d[49]), "=f"(d[50]), "=f"(d[51]), "=f"(d[52]), "=f"(d[53]), "=f"(d[54]), "=f"(d[55]),
          "=f"(d[56]), "=f"(d[57]), "=f"(d[58]), "=f"(d[59]), "=f"(d[60]), "=f"(d[61]), "=f"(d[62]), "=f"(d[63]),
          "=f"(d[64]), "=f"(d[65]), "=f"(d[66]), "=f"(d[67]), "=f"(d[68]), "=f"(d[69]), "=f"(d[70]), "=f"(d[71]),
          "=f"(d[72]), "=f"(d[73]), "=f"(d[74]), "=f"(d[75]), "=f"(d[76]), "=f"(d[77]), "=f"(d[78]), "=f"(d[79]),
          "=f"(d[80]), "=f"(d[81]), "=f"(d[82]), "=f"(d[83]), "=f"(d[84]), "=f"(d[85]), "=f"(d[86]), "=f"(d[87]),
          "=f"(d[88]), "=f"(d[89]), "=f"(d[90]), "=f"(d[91]), "=f"(d[92]), "=f"(d[93]), "=f"(d[94]), "=f"(d[95]),
          "=f"(d[96]), "=f"(d[97]), "=f"(d[98]), "=f"(d[99]), "=f"(d[100]), "=f"(d[101]), "=f"(d[102]), "=f"(d[103]),
          "=f"(d[104]), "=f"(d[105]), "=f"(d[106]), "=f"(d[107]), "=f"(d[108]), "=f"(d[109]), "=f"(d[110]), "=f"(d[111]),
          "=f"(d[112]), "=f"(d[113]), "=f"(d[114]), "=f"(d[115]), "=f"(d[116]), "=f"(d[117]), "=f"(d[118]), "=f"(d[119]),
          "=f"(d[120]), "=f"(d[121]), "=f"(d[122]), "=f"(d[123]), "=f"(d[124]), "=f"(d[125]), "=f"(d[126]), "=f"(d[127])
        : "l"(da), "l"(db));
}
__device__ __forceinline__ void wgmma_n256(float (&d)[128], uint64_t da, uint64_t db) {
    asm volatile("{\n.reg .pred p;\nsetp.eq.b32 p, 0, 0;\n"
        "wgmma.mma_async.sync.aligned.m64n256k16.f32.bf16.bf16 {"
        "%0, %1, %2, %3, %4, %5, %6, %7, %8, %9, %10, %11, %12, %13, %14, %15, "
        "%16, %17, %18, %19, %20, %21, %22, %23, %24, %25, %26, %27, %28, %29, %30, %31, "
        "%32, %33, %34, %35, %36, %37, %38, %39, %40, %41, %42, %43, %44, %45, %46, %47, "
        "%48, %49, %50, %51, %52, %53, %54, %55, %56, %57, %58, %59, %60, %61, %62, %63, "
        "%64, %65, %66, %67, %68, %69, %70, %71, %72, %73, %74, %75, %76, %77, %78, %79, "
        "%80, %81, %82, %83, %84, %85, %86, %87, %88, %89, %90, %91, %92, %93, %94, %95, "
        "%96, %97, %98, %99, %100, %101, %102, %103, %104, %105, %106, %107, %108, %109, %110, %111, "
        "%112, %113, %114, %115, %116, %117, %118, %119, %120, %121, %122, %123, %124, %125, %126, %127"
        "}, %128, %129, p, 1, 1, 0, 1;\n}\n"
        : "+f"(d[0]), "+f"(d[1]), "+f"(d[2]), "+f"(d[3]), "+f"(d[4]), "+f"(d[5]), "+f"(d[6]), "+f"(d[7]),
          "+f"(d[8]), "+f"(d[9]), "+f"(d[10]), "+f"(d[11]), "+f"(d[12]), "+f"(d[13]), "+f"(d[14]), "+f"(d[15]),
          "+f"(d[16]), "+f"(d[17]), "+f"(d[18]), "+f"(d[19]), "+f"(d[20]), "+f"(d[21]), "+f"(d[22]), "+f"(d[23]),
          "+f"(d[24]), "+f"(d[25]), "+f"(d[26]), "+f"(d[27]), "+f"(d[28]), "+f"(d[29]), "+f"(d[30]), "+f"(d[31]),
          "+f"(d[32]), "+f"(d[33]), "+f"(d[34]), "+f"(d[35]), "+f"(d[36]), "+f"(d[37]), "+f"(d[38]), "+f"(d[39]),
          "+f"(d[40]), "+f"(d[41]), "+f"(d[42]), "+f"(d[43]), "+f"(d[44]), "+f"(d[45]), "+f"(d[46]), "+f"(d[47]),
          "+f"(d[48]), "+f"(d[49]), "+f"(d[50]), "+f"(d[51]), "+f"(d[52]), "+f"(d[53]), "+f"(d[54]), "+f"(d[55]),
          "+f"(d[56]), "+f"(d[57]), "+f"(d[58]), "+f"(d[59]), "+f"(d[60]), "+f"(d[61]), "+f"(d[62]), "+f"(d[63]),
          "+f"(d[64]), "+f"(d[65]), "+f"(d[66]), "+f"(d[67]), "+f"(d[68]), "+f"(d[69]), "+f"(d[70]), "+f"(d[71]),
          "+f"(d[72]), "+f"(d[73]), "+f"(d[74]), "+f"(d[75]), "+f"(d[76]), "+f"(d[77]), "+f"(d[78]), "+f"(d[79]),
          "+f"(d[80]), "+f"(d[81]), "+f"(d[82]), "+f"(d[83]), "+f"(d[84]), "+f"(d[85]), "+f"(d[86]), "+f"(d[87]),
          "+f"(d[88]), "+f"(d[89]), "+f"(d[90]), "+f"(d[91]), "+f"(d[92]), "+f"(d[93]), "+f"(d[94]), "+f"(d[95]),
          "+f"(d[96]), "+f"(d[97]), "+f"(d[98]), "+f"(d[99]), "+f"(d[100]), "+f"(d[101]), "+f"(d[102]), "+f"(d[103]),
          "+f"(d[104]), "+f"(d[105]), "+f"(d[106]), "+f"(d[107]), "+f"(d[108]), "+f"(d[109]), "+f"(d[110]), "+f"(d[111]),
          "+f"(d[112]), "+f"(d[113]), "+f"(d[114]), "+f"(d[115]), "+f"(d[116]), "+f"(d[117]), "+f"(d[118]), "+f"(d[119]),
          "+f"(d[120]), "+f"(d[121]), "+f"(d[122]), "+f"(d[123]), "+f"(d[124]), "+f"(d[125]), "+f"(d[126]), "+f"(d[127])
        : "l"(da), "l"(db));
}
template <int O, int L>
__device__ __forceinline__ void wgmma_n64(float (&d)[L], uint64_t da, uint64_t db) {
    asm volatile("{\n.reg .pred p;\nsetp.eq.b32 p, 0, 0;\n"
        "wgmma.mma_async.sync.aligned.m64n64k16.f32.bf16.bf16 {%0, %1, %2, %3, %4, %5, %6, %7, %8, %9, %10, %11, %12, %13, %14, %15, %16, %17, %18, %19, %20, %21, %22, %23, %24, %25, %26, %27, %28, %29, %30, %31}, %32, %33, p, 1, 1, 0, 1;\n}\n"
        : "+f"(d[O + 0]), "+f"(d[O + 1]), "+f"(d[O + 2]), "+f"(d[O + 3]), "+f"(d[O + 4]), "+f"(d[O + 5]), "+f"(d[O + 6]), "+f"(d[O + 7]),
          "+f"(d[O + 8]), "+f"(d[O + 9]), "+f"(d[O + 10]), "+f"(d[O + 11]), "+f"(d[O + 12]), "+f"(d[O + 13]), "+f"(d[O + 14]), "+f"(d[O + 15]),
          "+f"(d[O + 16]), "+f"(d[O + 17]), "+f"(d[O + 18]), "+f"(d[O + 19]), "+f"(d[O + 20]), "+f"(d[O + 21]), "+f"(d[O + 22]), "+f"(d[O + 23]),
          "+f"(d[O + 24]), "+f"(d[O + 25]), "+f"(d[O + 26]), "+f"(d[O + 27]), "+f"(d[O + 28]), "+f"(d[O + 29]), "+f"(d[O + 30]), "+f"(d[O + 31])
        : "l"(da), "l"(db));
}


struct Idx {
    uint32_t lane, warp, w4, q4, g8, prow, pan;
    __device__ __forceinline__ Idx() {
        uint32_t t; asm volatile("mov.u32 %0, %%tid.x;" : "=r"(t));
        lane = t & 31; warp = t >> 5; w4 = warp & 3; q4 = lane & 3; g8 = lane >> 2;
        prow = w4 * 16 + ((lane >> 3) & 1) * 8 + (lane & 7);
        pan = prow * 128 + (((lane >> 4) ^ (lane & 7)) << 4);
    }
};
#define IDX() const Idx ix; const uint32_t lane = ix.lane, warp = ix.warp, w4 = ix.w4, q4 = ix.q4, g8 = ix.g8, prow = ix.prow, pan_addr = ix.pan; \
    (void)lane; (void)warp; (void)w4; (void)q4; (void)g8; (void)prow; (void)pan_addr;

struct Ring {
    uint32_t slot, par;
    __device__ __forceinline__ void next() { if (++slot == NSLOT) { slot = 0; par ^= 1; } }
};
__device__ __forceinline__ uint32_t BAR_FULL(uint32_t sb, uint32_t s) { return sb + OFF_BAR + 8 * s; }
__device__ __forceinline__ uint32_t BAR_EMPTY(uint32_t sb, uint32_t s) { return sb + OFF_BAR + 48 + 8 * s; }
__device__ __forceinline__ uint32_t BAR_SFULL(uint32_t sb, uint32_t i) { return sb + OFF_BAR + 96 + 8 * i; }
__device__ __forceinline__ uint32_t BAR_ONE(uint32_t sb, uint32_t i) { return sb + OFF_BAR + 128 + 8 * i; }
enum { EV_X1, EV_WIN, EV_WINL = EV_WIN + 3, EV_X, EV_ST0, EV_GA, EV_GB, EV_P2, EV_LAG0, EV_LAG1, EV_LAG2, EV_LAG3, EV_LAG4, EV_LAG5, EV_HB, EV_H, EV_H1, EV_H2, EV_SENT, EV_SEC, EV_BACK, EV_BACK1, EV_A0, EV_A0L = EV_A0 + 3, EV_PAR, EV_COUNT };

static_assert(128 + 8 * EV_COUNT <= 384, "");

enum { K_ABS, K_OWN, K_PANEL };
enum { F_WRAP = 1, F_TWICE = 2, F_SKIP = 4, F_EARLY = 8 };
constexpr uint32_t pre_ev(uint32_t ev) { return 128 + 8 * ev; }
constexpr uint32_t pre_sfull(uint32_t i, uint32_t par) { return 96 + 8 * i + par; }
constexpr uint4 seg(uint32_t n, uint32_t kind, uint32_t a, uint32_t step, uint32_t q, uint32_t jump, uint32_t flags, uint32_t map, uint32_t kb, uint32_t pre = 0,
                    uint32_t blkj = 0, uint32_t blk = 0, uint32_t split = 0, uint32_t cnt = 0) {
    return uint4{n | (127 + q) / q << 8 | flags << 16 | map << 24, kind | a << 2 | step << 16 | jump / 64 << 24, kb | blkj << 8 | blk << 12 | split << 20, pre | cnt << 24};
}
constexpr int NSEG = 14;
__device__ const uint4 g_sched[3][NSEG] = {
    {seg(NSLOT, K_ABS, 0, 0, 1, 0, F_SKIP, L_WQKV, 0),
     seg(27 - 2 * NQ, K_PANEL, 1, 32, 2, 64, 0, L_WQKV, 24, 0, 2, 0, 1), seg(2 * NQ, K_PANEL, 28 - 2 * NQ, 32, 2, 64, 0, L_WKV, 16, 0, 2, 0, 1),
     seg(NQ, K_PANEL, 28 - 2 * NQ, 64, 1, 64, 0, L_WQ, 16, 0, 2, 0, 3), seg(NS, K_PANEL, 28 - 2 * NQ - 2 * NS, 64, 1, 64, 0, L_WQ1, 8, 0, 2, 1, 4),
     seg(2, K_OWN, 0, 64, 32, 0, 0, L_WO, 16, 0, 2, 0, 3), seg(14, K_PANEL, 0, 64, 1, 64, 0, L_WO, 16, 0, 2, 0, 3),
     seg(4, K_OWN, 0, 32, 32, 0, F_TWICE, L_WG, 24, 0, 7, 0, 2), seg(28, K_PANEL, 0, 32, 2, 64, F_WRAP, L_WG, 24, 0, 7, 0, 2),
     seg(32, K_ABS, 0, 32, 32, 0, 0, L_WG, 16, 0, 7, 3, 2), seg(32, K_ABS, 0, 32, 32, 0, 0, L_WG, 16, 0, 7, 5, 2),
     seg(24, K_ABS, 0, 64, 3, 256, 0, L_WD, 16, 0, 2, 0, 3), seg(16, K_ABS, 6, 64, 2, 320, 0, L_WD, 16, 0, 2, 0, 3), seg(16, K_ABS, 10, 64, 2, 320, 0, L_WD, 16, 0, 2, 0, 3)},
    {seg(28, K_PANEL, 0, 32, 2, 64, F_EARLY, L_H1, 8, pre_sfull(2, 0), 0, 0, 0, 1),
     seg(NQ, K_PANEL, 28 - 2 * NQ, 64, 1, 64, 0, L_H1Q, 16), seg(NS, K_PANEL, 28 - 2 * NQ - 2 * NS, 64, 1, 64, 0, L_H1Q, 16),
     seg(2, K_OWN, 0, 64, 32, 0, 0, L_X, 16), seg(14, K_PANEL, 0, 64, 1, 64, 0, L_O, 16, pre_sfull(0, 1), 0, 0, 0, 2),
     seg(28, K_PANEL, 0, 32, 2, 64, F_EARLY, L_H2, 8, pre_sfull(2, 0), 0, 0, 0, 3),
     seg(32, K_ABS, 0, 32, 32, 0, 0, L_H2, 8, pre_ev(EV_SENT)), seg(32, K_ABS, 0, 32, 32, 0, 0, L_H2, 8),
     seg(24, K_ABS, 0, 64, 3, 256, 0, L_HB, 16, pre_ev(EV_H)), seg(16, K_ABS, 6, 64, 2, 320, 0, L_HB, 16, pre_ev(EV_H1)), seg(16, K_ABS, 10, 64, 2, 320, 0, L_HB, 16, pre_ev(EV_H2))},
    {seg(16, K_ABS, 0, 64, 32, 0, 0, L_WMOD, 32, 0, 4, 32), seg(16, K_ABS, 0, 64, 32, 0, 0, L_WMOD, 32, 0, 4, 48),
     seg(16, K_ABS, 0, 64, 32, 0, 0, L_WMOD, 32, 0, 4, 64), seg(16, K_ABS, 0, 64, 32, 0, 0, L_WMOD, 32, 0, 4, 80)}};

struct Pipe {
    uint32_t sb, slot, par, tok, rel;
    __device__ __forceinline__ void arm() {
        uint32_t t, a; asm volatile("mov.u32 %0, %%tid.x;" : "=r"(t));
        asm("mapa.shared::cluster.u32 %0, %1, %2;" : "=r"(a) : "r"(BAR_EMPTY(sb, 0)), "r"((t >> 5) & 1));
        tok = __shfl_sync(0xffffffffu, (t & 95u) == 0 ? a : 0, t & 31);
    }
    __device__ __forceinline__ uint32_t stage() {
        mbar_wait(BAR_FULL(sb, slot), par);
        return d16(sb) + slot * (SLOT >> 4);
    }
    __device__ __forceinline__ void release() { if (rel) asm volatile("mbarrier.arrive.shared::cluster.b64 _, [%0];" :: "r"(rel) : "memory"); rel = 0; }
    __device__ __forceinline__ void issued() {
        wg_commit(); wg_wait<1>(); release();
        if (tok) rel = tok + 8 * slot;
        if (++slot == NSLOT) { slot = 0; par ^= 1; }
    }
    __device__ __forceinline__ void drain() { wg_wait<0>(); release(); }
    __device__ __forceinline__ void at(int stage) { slot = stage % NSLOT; par = (stage / NSLOT) & 1; }
};
enum { M_QKV, M_Q0KV, M_KV, M_GU3, M_GU2 };
template <int MODE, bool ZERO, bool OWN = false>
__device__ __forceinline__ void step32(float (&a256)[128], float (&a128)[64], Pipe& p, uint32_t wg, uint32_t own = 0) {
    constexpr uint32_t KS = MODE < M_KV ? 12288 : MODE == M_KV ? 8192 : 2048, LBO = MODE <= M_KV ? 2048 : 4096;
    constexpr uint32_t O256 = 8192 + (MODE < M_KV ? 4096 : 0), O128 = 8192 + (MODE < M_KV ? 0 : 16384);
    constexpr bool W128 = MODE == M_QKV || MODE == M_GU3;
    const uint32_t st = p.stage();
    wg_fence();
#pragma unroll
    for (int k = 0; k < 2; ++k) {
        const uint64_t da = OWN ? mk_desc(own, k * 32, 16, 1024, 1) : mk_desc(st + wg * 256, k * 32, 16, 512, 2);
        const uint64_t d0 = mk_desc(st, O256 + k * KS, LBO, 1024, 1), d1 = mk_desc(st, O128 + k * KS, LBO, 1024, 1);
        if (ZERO && k == 0) { wgmma_n256_z(a256, da, d0); if (W128) wgmma_n128_z(a128, da, d1); }
        else { wgmma_n256(a256, da, d0); if (W128) wgmma_n128(a128, da, d1); if (MODE == M_Q0KV) wgmma_n64<0>(a128, da, d1); }
    }
    p.issued();
}
struct Nop { __device__ __forceinline__ void operator()() const {} };
template <bool ZERO, class F = Nop>
__device__ __forceinline__ void step64(float (&acc)[64], Pipe& p, uint32_t wg, int own = -1, F landed = F()) {
    const uint32_t st = p.stage();
    landed();
    const uint32_t sa = own >= 0 ? d16(p.sb) + OFF_STG / 16 + wg * 512 + own * 1024 : st + wg * 512;
    wg_fence();
#pragma unroll
    for (int k = 0; k < 4; ++k) {
        const uint64_t da = mk_desc(sa, k * 32, 16, 1024, 1), db = mk_desc(st, 16384 + k * 2048, 8192, 1024, 1);
        if (ZERO && k == 0) wgmma_n128_z(acc, da, db); else wgmma_n128(acc, da, db);
    }
    p.issued();
}
__device__ __forceinline__ void run64_landed(float (&acc)[64], Pipe& p, uint32_t wg, int n) {
#pragma unroll 1
    while (true) {
        const uint32_t st = d16(p.sb) + p.slot * (SLOT >> 4);
        wg_fence();
#pragma unroll
        for (int k = 0; k < 4; ++k) wgmma_n128(acc, mk_desc(st + wg * 512, k * 32, 16, 1024, 1), mk_desc(st, 16384 + k * 2048, 8192, 1024, 1));
        p.issued();
        if (--n == 0) break;
        p.stage();
    }
}
__device__ __forceinline__ void rename(float (&d)[64], const float (&a)[64]) {
#pragma unroll
    for (int i = 0; i < 64; ++i) asm volatile("mov.b32 %0, %1;" : "=f"(d[i]) : "f"(a[i]));
}
template <int MODE, int ST>
__device__ __forceinline__ void run_own(float (&a256)[128], float (&a128)[64], Pipe& p, uint32_t wg) {
    const uint32_t a0 = d16(p.sb) + OFF_OWN / 16 + wg * 512;
    p.at(ST);
    step32<MODE, true, true>(a256, a128, p, wg, a0);
#pragma unroll 1
    for (int i = 1; i < 4; ++i) step32<MODE, false, true>(a256, a128, p, wg, a0 + (i >> 1) * 1024 + (i & 1) * 4);
    p.drain();
    mbar_arrive_if0(BAR_FULL(p.sb, 5), threadIdx.x & 127);
#pragma unroll 1
    for (int i = 0; i < 4; ++i) {
        if (i < 2) p.at(i ? ST + 6 : ST + 4);
        if (wg == 0) mbar_wait(BAR_ONE(p.sb, EV_A0 + i), ST > 0);
        step32<MODE, false>(a256, a128, p, wg);
    }
    p.at(ST + 9);
}
template <int LG, class Step>
__device__ __forceinline__ void run(int n, uint32_t wg, uint32_t ev, Step step) {
    const int last = LG ? (wg ? EARLY : LG) : 0;
#pragma unroll 1
    for (int part = 0; ; ++part) {
#pragma unroll 1
        for (int i = part ? last : n - last; i > 0; --i) step();
        if (part || !LG) break;
        mbar_arrive_if0(ev, threadIdx.x ^ 128);
        if (wg == 0) mbar_wait(ev, 0);
    }
}

struct LnRow { float rs0, nm0, rs1, nm1; };
__device__ __forceinline__ void publish_stats(uint4* dst, float s0, float q0, float s1, float q1, uint32_t tag) {
    st_pkt16(dst, (__float_as_uint(s0) & ~3u) | tag, __float_as_uint(s1), __float_as_uint(q0), __float_as_uint(q1));
}
template <class F = Nop>
__device__ __forceinline__ LnRow merge_stats(const uint4* src, uint32_t tag, F meanwhile = F()) {
    uint4 a = ld_pkt16(src), b = ld_pkt16(src + S_ / 2);
    meanwhile();
    while (!__all_sync(0xffffffffu, (a.x & b.x & tag) != 0)) { a = ld_pkt16(src); b = ld_pkt16(src + S_ / 2); }
    float v[4] = {__uint_as_float(a.x) + __uint_as_float(b.x), __uint_as_float(a.y) + __uint_as_float(b.y),
                  __uint_as_float(a.z) + __uint_as_float(b.z), __uint_as_float(a.w) + __uint_as_float(b.w)};
#pragma unroll
    for (int o = 1; o < 4; o <<= 1)
#pragma unroll
        for (int i = 0; i < 4; ++i) v[i] += __shfl_xor_sync(0xffffffffu, v[i], o);
    const float m0 = v[0] * (1.f / D_), m1 = v[1] * (1.f / D_);
    const float r0 = rsq(fmaxf(fmaf(-m0, m0, v[2] * (1.f / D_)), 0.f) + 1e-5f), r1 = rsq(fmaxf(fmaf(-m1, m1, v[3] * (1.f / D_)), 0.f) + 1e-5f);
    return LnRow{r0, -m0 * r0, r1, -m1 * r1};
}
__device__ __forceinline__ void ln_norm(uint32_t (&y)[32], const float (&x)[64], const LnRow& n) {
#pragma unroll
    for (int e = 0; e < 32; ++e) {
        const float rs = (e & 1) ? n.rs1 : n.rs0, nm = (e & 1) ? n.nm1 : n.nm0;
        y[e] = pack2(fmaf(x[2 * e], rs, nm), fmaf(x[2 * e + 1], rs, nm));
    }
}
__device__ __forceinline__ void ln_emit(const uint32_t (&y)[32], const uint4 (&p)[8], uint32_t sb, uint32_t wg, const Idx& ix) {
#pragma unroll
    for (int i = 0; i < 8; ++i) {
        uint32_t r[4];
#pragma unroll
        for (int e = 0; e < 4; ++e) r[e] = hfma2_bf16(y[4 * i + e], e < 2 ? p[i].z : p[i].w, e < 2 ? p[i].x : p[i].y);
        stsm4(sb + OFF_OWN + wg * 8192 + (i >> 2) * 16384 + (ix.pan ^ ((i & 3) << 5)), r[0], r[1], r[2], r[3]);
        if (i == 3) { __syncwarp(); if (ix.lane == 0) mbar_arrive(BAR_SFULL(sb, wg * 2)); }
    }
    fence_async_smem();
    __syncwarp();
    if (ix.lane == 0) mbar_arrive(BAR_SFULL(sb, wg * 2 + 1));
    bar_sync(1 + wg, 128);
}
template <int P>
__device__ __forceinline__ void load_panel(uint32_t (&r)[32], uint32_t p) {
    IDX();
#pragma unroll
    for (int i = 4 * P; i < 4 * P + 4; ++i) ldsm4(p + (pan_addr ^ ((i & 3) << 5)), r[4 * i], r[4 * i + 1], r[4 * i + 2], r[4 * i + 3]);
}
template <int E0 = 0, int E1 = 32>
__device__ __forceinline__ void widen(float (&x)[64], const uint32_t (&r)[32]) {
#pragma unroll
    for (int e = E0; e < E1; ++e) asm volatile("shl.b32 %0, %2, 16;\nand.b32 %1, %2, 0xFFFF0000;" : "=&f"(x[2 * e]), "=f"(x[2 * e + 1]) : "r"(r[e]));
}
template <int I0 = 0, int I1 = 8>
__device__ __forceinline__ void load_table(uint4 (&t)[8], uint32_t tab) {
#pragma unroll
    for (int i = I0; i < I1; ++i) t[i] = lds128(tab + i * 64 + (threadIdx.x & 3) * 16);
}
template <int STRIDE, int P0, int P1, class Step>
__device__ __forceinline__ void epilogue_operands(float (&x)[64], uint4 (&g)[8], uint32_t (&r)[32], uint32_t src, uint32_t tab, Step step) {
#pragma unroll
    for (int i = 0; i < 64; ++i) asm volatile("" : "=f"(x[i]));
#pragma unroll
    for (int i = 0; i < (P1 > 6 ? 8 : 0); ++i) asm volatile("" : "=r"(g[i].x), "=r"(g[i].y), "=r"(g[i].z), "=r"(g[i].w));
#pragma unroll 1
    for (int it = P0 * STRIDE; it < P1 * STRIDE; ++it) {
        step([&] {
            if (it == 0) load_panel<0>(r, src);
            if (it == STRIDE) load_panel<1>(r, src + 16384);
            if (it == 6 * STRIDE) load_table<0, 4>(g, tab);
            if (it == 7 * STRIDE) load_table<4, 8>(g, tab);
        });
        if (it == 2 * STRIDE) widen<0, 8>(x, r);
        if (it == 3 * STRIDE) widen<8, 16>(x, r);
        if (it == 4 * STRIDE) widen<16, 24>(x, r);
        if (it == 5 * STRIDE) widen<24, 32>(x, r);
    }
}
__device__ __forceinline__ float gate_of(const uint4 (&t)[8], int e) {
    const uint4 v = t[e >> 3];
    return __uint_as_float((e & 4) ? ((e & 1) ? v.w : v.z) : ((e & 1) ? v.y : v.x));
}
__device__ __forceinline__ constexpr int glu_at(int i, int e) { return (i >> 2) * 64 + ((i >> 1) & 1) * 16 + (e >> 1) * 4 + (i & 1) * 2 + (e & 1); }
struct Raw { const float (&a)[64]; __device__ __forceinline__ float operator()(int e) const { return a[e]; } };
struct Packed {
    const uint32_t (&a)[64];
    __device__ __forceinline__ float operator()(int e) const {
        float v;
        if (e & 1) asm volatile("and.b32 %0, %1, 0xFFFF0000;" : "=f"(v) : "r"(a[e >> 1])); else asm volatile("shl.b32 %0, %1, 16;" : "=f"(v) : "r"(a[e >> 1]));
        return v;
    }
};
template <class A>
__device__ __forceinline__ void glu_tanh(float (&t)[8], A a, int i) {
#pragma unroll
    for (int e = 0; e < 8; ++e) asm volatile("tanh.approx.f32 %0, %1;" : "=f"(t[e]) : "f"(a(glu_at(i, e))));
}
template <bool FENCE, class A>
__device__ __forceinline__ void glu_store(const float (&t)[8], A a, int i, __nv_bfloat16* dst) {
    uint32_t r[4];
#pragma unroll
    for (int c = 0; c < 4; ++c) {
        const float u0 = a(32 + glu_at(i, 2 * c)), u1 = a(33 + glu_at(i, 2 * c));
        r[c] = pack2(fmaf(t[2 * c], u0, u0), fmaf(t[2 * c + 1], u1, u1));
    }
    if (!FENCE) asm volatile("st.global.v4.u32 [%0], {%1, %2, %3, %4};" :: "l"(dst + (i & 1) * 8 * F_ + (i >> 1) * 32), "r"(r[0]), "r"(r[1]), "r"(r[2]), "r"(r[3]) : "memory");
    else asm volatile("{\n.reg .pred p;\nsetp.eq.u32 p, %5, %6;\nG_LOOP:\nst.global.v4.u32 [%0], {%1, %2, %3, %4};\n@p bra G_LOOP;\n}"
        :: "l"(dst + (i & 1) * 8 * F_ + (i >> 1) * 32), "r"(r[0]), "r"(r[1]), "r"(r[2]), "r"(r[3]), "r"(blockIdx.y), "r"(1000 + i) : "memory");
}
__device__ __forceinline__ void glu_now(const float (&a)[64], __nv_bfloat16* dst) {
    float t[2][8];
#pragma unroll
    for (int i = 0; i <= 4; ++i) {
        if (i < 4) glu_tanh(t[i & 1], Raw{a}, i);
        if (i > 0) glu_store<true>(t[(i - 1) & 1], Raw{a}, i - 1, dst);
    }
}
template <class Step>
__device__ __forceinline__ void glu_under(uint32_t (&a)[64], __nv_bfloat16* dst, int n, Step step) {
#pragma unroll 1
    for (int it = -n; it < 16; ++it) {
        step();
        if (it >= 0 && !(it & 1)) {
#pragma unroll
            for (int i = 0; i < 4; ++i)
                if ((it & 7) == 2 * i) {
                    float t[8];
                    glu_tanh(t, Packed{a}, i); glu_store<false>(t, Packed{a}, i, dst);
#pragma unroll
                    for (int c = 0; c < 8; ++c) { const int e = (glu_at(i, (2 * c) & 7) >> 1) + (c >> 2) * 16; a[e] = a[32 + e]; }
                    if (i == 3) dst += 64;
                }
        }
    }
}
__device__ __forceinline__ void pack_all(uint32_t (&d)[64], const float (&a)[128]) {
#pragma unroll
    for (int i = 0; i < 64; ++i) d[i] = pack2(a[2 * i], a[2 * i + 1]);
}

__global__ void __launch_bounds__(384, 1)
fused_block_kernel(const __grid_constant__ Ptrs pt, const __grid_constant__ Maps mp) {
    uint32_t* const g_flags = pt.mail->flags;
    uint2* const g_mod = pt.mail->mod;
    uint4* const g_st1 = pt.mail->st1;
    uint32_t* const g_par2 = pt.mail->par2;
    uint4* const g_halo = pt.mail->halo;
    const __nv_bfloat16* __restrict__ cvec = pt.c;
    if (threadIdx.x == 224) { prefetch_map(&mp.x); prefetch_map(&mp.wm); }
    uint32_t ep = 0;
#define LOAD_EP() asm volatile("ld.relaxed.gpu.global.u32 %0, [%1];" : "=r"(ep) : "l"(&g_flags[FL_DONE + (threadIdx.x & blockIdx.y)]) : "memory")
    if (threadIdx.x >= 256) LOAD_EP();
    extern __shared__ __align__(1024) uint8_t smem[];
    const uint32_t sb = smem_u32(smem) + 1024;
    const uint32_t tid = threadIdx.x, tw = tid & 127, lane = tid & 31;
    const uint32_t warp = __shfl_sync(0xffffffffu, tid >> 5, 0), wg = warp >> 2;
    uint32_t rank; asm("mov.u32 %0, %%cluster_ctarank;" : "=r"(rank));
    rank = __shfl_sync(0xffffffffu, rank, 0);
    uint32_t smid; asm volatile("mov.u32 %0, %%smid;" : "=r"(smid));
    const int c = __shfl_sync(0xffffffffu, smid >> 1, 0);
    const int q7 = ((c - 32) * 37) >> 8;
    const bool aux = (c >> 1) == 30;
    const int grp = c < 32 ? c & 7 : c < 60 ? c - 31 - 7 * q7 : 0;
    const int jhi = aux ? (c - 60) * 2 + rank : c - 58, jlo = c < 32 ? c >> 3 : 4 + q7, j = c < 60 ? jlo : jhi;
    const int m = grp * 2 + rank;
    const int cid = (c < 60 ? c : c - 2) * 2 + rank;
    if (warp == 1 && !aux && elect_one()) {
        mbar_init(BAR_ONE(sb, EV_X1), 1);
        mbar_expect_tx(BAR_ONE(sb, EV_X1), 16384);
#pragma unroll
        for (int i = 0; i < 2; ++i) tma_load(sb + OFF_STG + i * 16384 + 8192, &mp.x, D_ + j * 128 + i * 64, m * 64, BAR_ONE(sb, EV_X1));
#pragma unroll
        for (int i = 0; i < 4; ++i) mbar_init(BAR_ONE(sb, EV_WIN + i), 1);
#pragma unroll
        for (int i = 0; i < 4; ++i) {
            mbar_expect_tx(BAR_ONE(sb, EV_WIN + i), 8192);
            tma_load(sb + OFF_OWN + i * 8192, &mp.wm, (cid >> 2) * 64, (cid & 3) * 256 + i * 64, BAR_ONE(sb, EV_WIN + i));
        }
        asm volatile("fence.mbarrier_init.release.cluster;" ::: "memory");
    }
    __syncwarp();

    bool cluster_arrive_early = false;
    if (wg < 2) {
      cluster_arrive();
      if (aux) {
        LOAD_EP();
        cluster_wait();
        ep = __shfl_sync(0xffffffffu, ep, 0) / NCTA + 1;
        Ring r{0, 0};
#pragma unroll 1
        for (int p = 0; p < 4; ++p) {
            float acc[64];
#pragma unroll
            for (int i = 0; i < 64; ++i) acc[i] = 0.f;
#pragma unroll 1
            for (int kc = 0; kc < 16; ++kc) {
                mbar_wait(BAR_FULL(sb, r.slot), r.par);
                wg_fence();
#pragma unroll
                for (int k = 0; k < 4; ++k)
                    wgmma_n128(acc, mk_desc(d16(sb) + kc * 64, OFF_STG + k * 32, 16, 0, 1), mk_desc(d16(sb) + r.slot * (SLOT >> 4) + wg * 1024, k * 2048, 8192, 1024, 1));
                wg_commit();
                wg_wait<0>();
                mbar_arrive_if0(BAR_EMPTY(sb, r.slot), tw);
                r.next();
            }
            if (tw < 32) {
                if (tw < 4) {
#pragma unroll
                    for (int jn = 0; jn < 16; ++jn) sts32(sb + OFF_TAB + wg * 256 + (jn * 4 + tw) * 4, pack2(acc[jn * 4], acc[jn * 4 + 1]));
                }
                __syncwarp();
#pragma unroll 1
                for (uint32_t t = wg * 64 + tw; t < wg * 64 + 64; t += 32) {
                    const uint32_t val = lds32(sb + OFF_TAB + t * 4);
                    const float one = p == 2 ? 1.f : 0.f;
                    if (p == 0 || p == 3) st_pkt(g_mod + (8 + p * 4 + j) * 128 + t, val, ep);
                    else g_par2[(j * 16 + (t >> 3)) * 16 + (t & 3) * 4 + (p - 1) * 2 + ((t >> 2) & 1)] = pack2(0.5f * bf_round(one + bf_lo(val)), 0.5f * bf_round(one + bf_hi(val)));
                }
                __syncwarp();
                if (tw == 0 && p == 2) asm volatile("red.release.gpu.global.add.u32 [%0], 1;" :: "l"(&g_flags[FL_LN2]) : "memory");
            }
        }
      } else {
        Pipe pp{sb, 0, 0, 0, 0};
        pp.arm();
        {
            IDX();
            uint4* const st1 = g_st1 + m * 64 + warp * 8 + g8;
            if (q4 == (g8 >> 1)) st_pkt16(st1 + j * (S_ / 2), 0, 0, 0, 0);
            cluster_wait();
            uint32_t xr[32];
            mbar_wait(BAR_ONE(sb, wg ? EV_X1 : EV_X), 0);
            float sm[4] = {0.f, 0.f, 0.f, 0.f}, g0[4] = {0.f, 0.f, 0.f, 0.f}, g1[4] = {0.f, 0.f, 0.f, 0.f};
#pragma unroll
            for (int i = 0; i < 8; ++i) {
                ldsm4(sb + OFF_STG + wg * 8192 + (i >> 2) * 16384 + (pan_addr ^ ((i & 3) << 5)), xr[4 * i], xr[4 * i + 1], xr[4 * i + 2], xr[4 * i + 3]);
                mma16816(sm, xr[4 * i], xr[4 * i + 1], xr[4 * i + 2], xr[4 * i + 3], 0x3F803F80u, 0x3F803F80u);
                mma16816(g0, xr[4 * i], xr[4 * i + 1], xr[4 * i + 2], xr[4 * i + 3], xr[4 * i], xr[4 * i + 2]);
                mma16816(g1, xr[4 * i], xr[4 * i + 1], xr[4 * i + 2], xr[4 * i + 3], xr[4 * i + 1], xr[4 * i + 3]);
            }
            if (q4 == (g8 >> 1))
                publish_stats(st1 + j * (S_ / 2), sm[0], (g8 & 1) ? g0[1] : g0[0], sm[2], (g8 & 1) ? g1[3] : g1[2], 1);
            float xf[64];
            widen(xf, xr);
            mbar_wait(BAR_ONE(sb, EV_WINL), 0);
            const LnRow n1 = merge_stats(st1 + q4 * S_, 1);
            mbar_arrive_if0(BAR_ONE(sb, EV_ST0), tid & 159);
            ln_norm(xr, xf, n1);
            asm volatile("setmaxnreg.inc.sync.aligned.u32 %0;" :: "n"(RC));
            mbar_wait(BAR_ONE(sb, EV_PAR), 0);
            uint4 par[8];
            load_table(par, sb + OFF_PAR);
            ln_emit(xr, par, sb, wg, ix);
        }
        uint32_t xr[32];
        {
            float qa[64];
            uint32_t kl[16], kh[16], kp[16];
            uint32_t v0[32], v1[32];
            {
                float kv[128];
                float q1[64], q2[64];
                run_own<M_QKV, 0>(kv, q1, pp, wg);
                run<0>(24 - 2 * NS - 2 * NQ, wg, 0, [&] { step32<M_QKV, false>(kv, q1, pp, wg); });
                pp.drain();
                rename(q2, q1);
                run<0>(2 * NS, wg, 0, [&] { step32<M_Q0KV, false>(kv, q2, pp, wg); });
                pp.drain();
                rename(qa, q2);
                run<LAGQ>(2 * NQ, wg, BAR_ONE(sb, EV_LAG0), [&] { step32<M_KV, false>(kv, qa, pp, wg); });
                pp.stage();
                pp.drain();
                IDX();
#pragma unroll
                for (int t = 0; t < 16; ++t) v1[(t >> 1) * 4 + 2 + (t & 1)] = movm(pack2(kv[66 + 4 * t], kv[67 + 4 * t]));
#pragma unroll
                for (int t = 0; t < 16; ++t) {
                    kl[t] = pack2(kv[4 * t], kv[4 * t + 1]); kh[t] = pack2(kv[4 * t + 2], kv[4 * t + 3]);
                    v1[(t >> 1) * 4 + (t & 1)] = pack2(kv[64 + 4 * t], kv[65 + 4 * t]);
                }
                if (w4 < 3) {
                    const uint32_t dst = sb + OFF_STG + wg * 8192 + (w4 >> 1) * 16384 + (w4 & 1) * 4096;
#pragma unroll
                    for (int i = 0; i < 4; ++i) sts128(dst + i * 512 + lane * 16, kh[4 * i], kh[4 * i + 1], kh[4 * i + 2], kh[4 * i + 3]);
#pragma unroll
                    for (int i = 0; i < 8; ++i) sts64(dst + 2048 + i * 256 + lane * 8, v1[4 * i + 2], v1[4 * i + 3]);
                } else if (m < 15) {
                    uint4* const dst = g_halo + (m * 8 + j) * 512 + wg * 256;
#pragma unroll
                    for (int i = 0; i < 4; ++i) { if (!kh[4 * i]) kh[4 * i] = 0x8000u; st_pkt16(dst + i * 32 + lane, kh[4 * i], kh[4 * i + 1], kh[4 * i + 2], kh[4 * i + 3]); }
#pragma unroll
                    for (int i = 0; i < 8; ++i) { if (!v1[4 * i + 2]) v1[4 * i + 2] = 0x8000u; st_pkt((uint2*)(dst + 128) + i * 32 + lane, v1[4 * i + 2], v1[4 * i + 3]); }
                }
            }
            pp.at(ST_Q);
            run64_landed(qa, pp, wg, QA);
            pp.stage();
            IDX();
            uint4* const halo = g_halo + ((m - 1) * 8 + j) * 512 + wg * 256;
            auto fetch_halo = [&] {
#pragma unroll
                for (int i = 0; i < 4; ++i) {
                    const uint4 t = m > 0 ? ld_pkt16(halo + i * 32 + lane) : make_uint4(0, 0, 0, 0);
                    kp[4 * i] = t.x; kp[4 * i + 1] = t.y; kp[4 * i + 2] = t.z; kp[4 * i + 3] = t.w;
                }
#pragma unroll
                for (int i = 0; i < 8; ++i) {
                    const uint2 t = m > 0 ? ld_pkt((const uint2*)(halo + 128) + i * 32 + lane) : make_uint2(0, 0);
                    v0[4 * i] = t.x; v0[4 * i + 1] = t.y;
                }
            };
            bar_sync(1 + wg, 128);
#pragma unroll
            for (int t = 0; t < 16; ++t) v1[(t >> 1) * 4 + (t & 1)] = movm(v1[(t >> 1) * 4 + (t & 1)]);
            if (w4 == 0) fetch_halo();
            else {
                const uint32_t src = sb + OFF_STG + wg * 8192 + ((w4 - 1) >> 1) * 16384 + ((w4 - 1) & 1) * 4096;
#pragma unroll
                for (int i = 0; i < 4; ++i) { const uint4 t = lds128(src + i * 512 + lane * 16); kp[4 * i] = t.x; kp[4 * i + 1] = t.y; kp[4 * i + 2] = t.z; kp[4 * i + 3] = t.w; }
#pragma unroll
                for (int i = 0; i < 8; ++i) { const uint2 t = lds64(src + 2048 + i * 256 + lane * 8); v0[4 * i] = t.x; v0[4 * i + 1] = t.y; }
            }
            pp.at(ST_Q + QA);
            run64_landed(qa, pp, wg, NQ - QA);
#pragma unroll
            for (int t = 0; t < 16; ++t) asm volatile("mov.b32 %0, %1;" : "=r"(v0[(t >> 1) * 4 + 2 + (t & 1)]) : "r"(v1[(t >> 1) * 4 + (t & 1)]));
            bar_sync(1 + wg, 128);
            if (w4 == 0 && m > 0) {
                while (true) {
                    bool ok = true;
#pragma unroll
                    for (int i = 0; i < 8; ++i) ok = ok && v0[4 * i] != 0 && kp[4 * (i & 3)] != 0;
                    if (__all_sync(0xffffffffu, ok)) break;
                    fetch_halo();
                }
            }
            pp.drain();
            float qb[64];
            rename(qb, qa);
            const bool lo0 = q4 * 2 > g8, lo1 = q4 * 2 + 1 > g8;
            const bool nopast = m == 0 && w4 == 0;
            const uint32_t lomask = (lo0 ? 0xFFFFu : 0u) | (lo1 ? 0xFFFF0000u : 0u);
            const float sl2 = 0.17677669529663687f * 1.4426950408889634f;
            const uint32_t oa = wg * 8192 + (w4 * 16 + (lane & 7)) * 128 + (((lane >> 3) ^ (lane & 7)) << 4);
#pragma unroll
            for (int hp = 0; hp < 2; ++hp) {
                if (hp) {
                    bar_sync(3, 256);
#pragma unroll 1
                    for (int it = 0; it < NS; ++it) {
                        pp.slot = (SWEEP >> (4 * it)) & 7; pp.par = (SWEEP >> (4 * it + 3)) & 1;
                        const uint32_t st = pp.stage();
                        wg_fence();
#pragma unroll
                        for (int k = 0; k < 4; ++k) wgmma_n64<32>(qb, mk_desc(st + wg * 512, k * 32, 16, 1024, 1), mk_desc(st, 16384 + k * 2048, 8192, 1024, 1));
                        pp.issued();
                        if (it == 0) pp.rel = 0;
                        if (it == SWO && pp.tok) asm volatile("mbarrier.arrive.shared::cluster.b64 _, [%0];" :: "r"(pp.tok + 8 * (SWEEP & 7)) : "memory");
                    }
                    mbar_wait(BAR_FULL(sb, ST_WO % NSLOT), (ST_WO / NSLOT) & 1);
                    pp.drain();
                    load_panel<0>(xr, sb + ST_WO % NSLOT * SLOT + wg * 8192);
                }
                float e0[4], e1[4], mx[4], sum[4];
#pragma unroll
                for (int hh = 0; hh < 2; ++hh) {
                    const int h = 2 * hp + hh;
                    uint32_t qf[8];
                    float s[3][4];
#pragma unroll
                    for (int i = 0; i < 8; ++i) qf[i] = pack2(qb[16 * h + 2 * i], qb[16 * h + 2 * i + 1]);
#pragma unroll
                    for (int nt = 0; nt < 3; ++nt) {
                        const uint32_t (&kk)[16] = nt == 0 ? kp : nt == 1 ? kl : kh;
                        s[nt][0] = s[nt][1] = s[nt][2] = s[nt][3] = 0.f;
                        mma16816(s[nt], qf[0], qf[1], qf[2], qf[3], kk[4 * h], kk[4 * h + 1]);
                        mma16816(s[nt], qf[4], qf[5], qf[6], qf[7], kk[4 * h + 2], kk[4 * h + 3]);
                    }
#pragma unroll
                    for (int hf = 0; hf < 2; ++hf) {
                        e0[2 * hh + hf] = lo0 ? ((hf == 0 && nopast) ? -INFINITY : s[hf][hf * 2]) : s[hf + 1][hf * 2];
                        e1[2 * hh + hf] = lo1 ? ((hf == 0 && nopast) ? -INFINITY : s[hf][hf * 2 + 1]) : s[hf + 1][hf * 2 + 1];
                        mx[2 * hh + hf] = fmaxf(e0[2 * hh + hf], e1[2 * hh + hf]);
                    }
                }
#pragma unroll
                for (int o = 1; o < 4; o <<= 1)
#pragma unroll
                    for (int u = 0; u < 4; ++u) mx[u] = fmaxf(mx[u], __shfl_xor_sync(0xffffffffu, mx[u], o));
#pragma unroll
                for (int u = 0; u < 4; ++u) {
                    const float c = -mx[u] * sl2;
                    e0[u] = ex2(fmaf(e0[u], sl2, c)); e1[u] = ex2(fmaf(e1[u], sl2, c));
                    sum[u] = e0[u] + e1[u];
                }
#pragma unroll
                for (int o = 1; o < 4; o <<= 1)
#pragma unroll
                    for (int u = 0; u < 4; ++u) sum[u] += __shfl_xor_sync(0xffffffffu, sum[u], o);
#pragma unroll
                for (int u = 0; u < 4; ++u) {
                    const int h = 2 * hp + (u >> 1), hf = u & 1;
                    const uint32_t (&vv)[32] = hf ? v1 : v0;
                    const float iv = rcp(sum[u]);
                    const uint32_t pr = pack2(e0[u] * iv, e1[u] * iv);
                    float o[2][4];
#pragma unroll
                    for (int t = 0; t < 2; ++t) {
                        o[t][0] = o[t][1] = o[t][2] = o[t][3] = 0.f;
                        mma16816(o[t], vv[8 * h + 4 * t], vv[8 * h + 4 * t + 1], vv[8 * h + 4 * t + 2], vv[8 * h + 4 * t + 3], pr & lomask, pr & ~lomask);
                    }
                    stsm4t(sb + OFF_STG + hp * 16384 + (oa ^ ((h & 1) << 6)) + hf * 1024, pack2(o[0][0], o[0][1]), pack2(o[0][2], o[0][3]), pack2(o[1][0], o[1][1]), pack2(o[1][2], o[1][3]));
                }
                __syncwarp();
                if (lane == 0) mbar_arrive(BAR_SFULL(sb, wg * 2 + hp));
            }
        }
        {
            float acc[64], xf[64];
            uint4 gt[8], par[8];
            fence_async_smem();
            bar_sync(3, 256);
            pp.at(ST_WO);
            mbar_wait(BAR_FULL(sb, (ST_WO + 1) % NSLOT), ((ST_WO + 1) / NSLOT) & 1);
            step64<true>(acc, pp, wg, 0, [&] { load_panel<1>(xr, sb + (ST_WO + 1) % NSLOT * SLOT + wg * 8192); });
            step64<false>(acc, pp, wg, 1);
            fence_async_smem();
            bar_sync(1 + wg, 128);
            mbar_wait(BAR_ONE(sb, EV_GA), 0);
            load_table(gt, sb + OFF_TAB);
            pp.drain();
            uint4* const pub = g_st1 + __shfl_sync(0xffffffffu, j * (S_ / 2) + m * 64 + (tid >> 2), lane);
            pp.at(ST_WO + 2);
            epilogue_operands<1, 2, 6>(xf, gt, xr, 0, sb + OFF_TAB, [&](auto f) { step64<false>(acc, pp, wg, -1, f); });
            run<LAGW>(10, wg, BAR_ONE(sb, EV_LAG4), [&] { step64<false>(acc, pp, wg); });
            pp.drain();
            float su[4] = {0.f, 0.f, 0.f, 0.f}, sq[4] = {0.f, 0.f, 0.f, 0.f};
#pragma unroll
            for (int e = 0; e < 64; ++e) {
                xf[e] = fmaf(gate_of(gt, e), acc[e], xf[e]);
                su[e & 3] += xf[e]; sq[e & 3] = fmaf(xf[e], xf[e], sq[e & 3]);
            }
            {
                float v[4] = {su[0] + su[1], sq[0] + sq[1], su[2] + su[3], sq[2] + sq[3]};
#pragma unroll
                for (int o = 1; o < 4; o <<= 1)
#pragma unroll
                    for (int i = 0; i < 4; ++i) v[i] += __shfl_xor_sync(0xffffffffu, v[i], o);
                if ((tid & 3) == 0) publish_stats(pub, v[0], v[1], v[2], v[3], 2);
            }
            IDX();
            mbar_wait(BAR_ONE(sb, EV_P2), 0);
#pragma unroll
            for (int i = 0; i < 8; ++i)
                stsm4(sb + OFF_STG + wg * 8192 + (i >> 2) * 16384 + (pan_addr ^ ((i & 3) << 5)), pack2(xf[8 * i], xf[8 * i + 1]), pack2(xf[8 * i + 2], xf[8 * i + 3]),
                      pack2(xf[8 * i + 4], xf[8 * i + 5]), pack2(xf[8 * i + 6], xf[8 * i + 7]));
            load_table(par, sb + OFF_PAR);
            const LnRow n2 = merge_stats(pub + ((int)q4 * 2 - j) * (S_ / 2), 2, [&] {
                mbar_wait(BAR_EMPTY(sb, (ST_GU - 1) % NSLOT), ((ST_GU - 1) / NSLOT) & 1);
            });
            ln_norm(xr, xf, n2);
            ln_emit(xr, par, sb, wg, ix);
        }
        {
            auto h_at = [&](int col) { IDX(); return pt.hb + (m * 128 + warp * 16 + g8) * F_ + j * 448 + col + q4 * 8; };
            uint32_t gu[64];
            {
                float a256[128], a128[64];
                run_own<M_GU3, ST_GU>(a256, a128, pp, wg);
                run<LAG>(24, wg, BAR_ONE(sb, EV_LAG1), [&] { step32<M_GU3, false>(a256, a128, pp, wg); });
                __nv_bfloat16* const dst = h_at(128);
                pp.drain();
                glu_now(a128, dst);
                pack_all(gu, a256);
            }
#pragma unroll 1
            for (int p = 0; p < 2; ++p) {
                float b256[128], none[64];
                pp.at(p ? ST_G1 + 32 : ST_G1);
                step32<M_GU2, true>(b256, none, pp, wg);
                glu_under(gu, h_at(p * 192), GW + wg, [&] { step32<M_GU2, false>(b256, none, pp, wg); });
                __syncwarp();
                mbar_arrive_if0(BAR_ONE(sb, EV_HB), lane);
                run<LAGS>(15 - GW - wg, wg, BAR_ONE(sb, EV_LAG2 + p), [&] { step32<M_GU2, false>(b256, none, pp, wg); });
                pp.drain();
                pack_all(gu, b256);
            }
            float acc[64], xf[64];
            uint4 gt[8];
            pp.at(ST_G1 + 64);
            step64<true>(acc, pp, wg);
            glu_under(gu, h_at(320), GD + wg, [&] { step64<false>(acc, pp, wg); });
            __syncwarp();
            mbar_arrive_if0(BAR_ONE(sb, EV_HB), lane);
            uint32_t x1[32];
#pragma unroll
            for (int i = 0; i < 32; ++i) asm volatile("" : "=r"(x1[i]));
            mbar_wait(BAR_ONE(sb, EV_GB), 0);
            epilogue_operands<2, 0, 8>(xf, gt, x1, sb + OFF_STG + wg * 8192, sb + OFF_TAB + 512, [&](auto f) { step64<false>(acc, pp, wg, -1, f); });
            const uint32_t rows = sb + OFF_STG + wg * 8192 + (warp & 3) * 2048;
            const uint32_t oa = __shfl_sync(0xffffffffu, rows + (lane & 7) * 128 + (((lane >> 3) ^ (lane & 7)) << 4), lane);
            run<LAGD>(23 - GD - wg, wg, BAR_ONE(sb, EV_LAG5), [&] { step64<false>(acc, pp, wg); });
            cluster_arrive();
            mbar_arrive_if0(BAR_SFULL(sb, wg * 2), lane);
            wg_wait<0>();
#pragma unroll
            for (int u = 0; u < 4; ++u) {
                const int p = u >> 1, hf = u & 1;
#pragma unroll
                for (int i = 0; i < 2; ++i) {
                    uint32_t r[4];
#pragma unroll
                    for (int t = 0; t < 4; ++t) {
                        const int e = 32 * p + 16 * i + 4 * t + 2 * hf;
                        r[t] = pack2(fmaf(gate_of(gt, e), acc[e], xf[e]), fmaf(gate_of(gt, e + 1), acc[e + 1], xf[e + 1]));
                    }
                    stsm4((oa ^ (i << 6)) + p * 16384 + hf * 1024, r[0], r[1], r[2], r[3]);
                }
                {
                    if (u < 3) asm volatile("{\n.reg .pred p;\nsetp.eq.u32 p, %0, %1;\nO_LOOP:\nfence.proxy.async.shared::cta;\n@p bra O_LOOP;\n}" :: "r"(blockIdx.y), "r"(2000 + u) : "memory");
                    else fence_async_smem();
                    __syncwarp();
                    if (elect_one()) tma_store(&mp.out, wg * D_ + j * 128 + p * 64, m * 64 + (warp & 3) * 16 + hf * 8, rows + p * 16384 + hf * 1024);
                }
            }
            bulk_commit();
        }
      }
    } else {
        const bool sil = aux || warp == 9 || warp == 10;
        uint4 cv;
        if (sil) cv = *(const uint4*)(cvec + ((aux ? warp : cid) & 3) * 256 + lane * 8);
        uint4* const modp = pt.mail->mod1 + (lane >> 2) * 2048 + (cid & 3) * 512 + ((cid >> 2) * 4 + (warp & 3)) * 4 + (lane & 3);
        if (!aux) st_pkt16(modp, 0, 0, 0, 0);
        uint4 sg = make_uint4(0, 0, 0, 0);
        if (lane < NSEG) sg = pt.sched[(aux ? 2 : warp == 11) * NSEG + lane];
        if (elect_one()) {
            if (warp == 8) {
                prefetch_map(&mp.ld[aux ? L_WMOD : L_WQKV]);
            } else if (warp < 11) {
#pragma unroll
                for (int i = 0; i < 3; ++i) mbar_init(BAR_FULL(sb, (warp - 9) * 3 + i), aux ? 1 : 2);
#pragma unroll
                for (int i = 0; i < 2; ++i) mbar_init(BAR_SFULL(sb, (warp - 9) * 2 + i), 4);
#pragma unroll
                for (int i = 0; i < 3; ++i) mbar_init(BAR_EMPTY(sb, (warp - 9) * 3 + i), aux ? 2 : 4);
            } else {
#pragma unroll
                for (int i = EV_X; i < EV_COUNT; ++i) mbar_init(BAR_ONE(sb, i), i == EV_HB ? 8 : i == EV_ST0 ? 4 : i == EV_P2 ? 2 : 1);
            }
            asm volatile("fence.mbarrier_init.release.cluster;" ::: "memory");
        }
        __syncwarp();
        cluster_arrive();
        cluster_wait();
        const bool el = elect_one();
        const int kown = j * 128;
        auto first_tiles = [&](int i0, int i1) {
#pragma unroll 1
            for (int i = i0; i < i1; ++i) {
                if (el && i < 4) mbar_arrive(BAR_FULL(sb, i));
                if (el) {
                    mbar_expect_tx(BAR_FULL(sb, i), 24576);
                    tma_load5_mc(sb + i * SLOT + 8192 + rank * 12288, &mp.ld[L_WQKV], 0, (i < 4 ? kown + i * 32 : j ? 0 : 128) + rank * 16, 2 * j, 0, 0, BAR_FULL(sb, i));
                }
            }
        };
        if (!aux && warp == 8) {
            mbar_wait(BAR_ONE(sb, EV_WIN), 0);
            if (el) {
                mbar_expect_tx(BAR_ONE(sb, EV_X), 16384);
#pragma unroll
                for (int i = 0; i < 2; ++i) tma_load(sb + OFF_STG + i * 16384, &mp.x, j * 128 + i * 64, m * 64, BAR_ONE(sb, EV_X));
            }
            first_tiles(0, NB0);
        }
        if (sil) {
            const uint32_t s0 = pack2(silu_(bf_lo(cv.x)), silu_(bf_hi(cv.x))), s1 = pack2(silu_(bf_lo(cv.y)), silu_(bf_hi(cv.y))),
                           s2 = pack2(silu_(bf_lo(cv.z)), silu_(bf_hi(cv.z))), s3 = pack2(silu_(bf_lo(cv.w)), silu_(bf_hi(cv.w)));
#pragma unroll
            for (int i = 0; i < 4; ++i) {
                const uint32_t row = aux ? 0 : (warp & 1) * 4 + i;
                sts128(sb + (aux ? OFF_STG + (warp & 3) * 4096 : 4 * SLOT) + (lane >> 3) * 1024 + row * 128 + (((lane & 7) ^ row) << 4), s0, s1, s2, s3);
            }
            fence_async_smem();
        }
        bar_sync(4, 128);
        if (!aux) {
            float acc[32];
#pragma unroll
            for (int i = 0; i < 32; ++i) acc[i] = 0.f;
#pragma unroll 1
            for (int h = 0; h < 4; ++h) {
                mbar_wait(BAR_ONE(sb, EV_WIN + h), 0);
                wg_fence();
#pragma unroll
                for (int k = 0; k < 4; ++k)
                    wgmma_n64<0>(acc, mk_desc(d16(sb) + h * 64, 4 * SLOT + (k >> 2) * 1024 + (k & 3) * 32, 16, 0, 1), mk_desc(d16(sb) + h * 512, OFF_OWN + k * 2048, 8192, 1024, 1));
                wg_commit();
            }
            ep = __shfl_sync(0xffffffffu, ep, 0) / NCTA + 1;
            wg_wait<0>();
            const uint32_t i = warp & 3;
            auto pick = [&](int e) { return __float_as_uint(i & 2 ? (i & 1 ? acc[24 + e] : acc[16 + e]) : (i & 1 ? acc[8 + e] : acc[e])); };
            st_pkt16(modp, (pick(0) & ~3u) | (1 + (ep & 1)), pick(1), pick(4), pick(5));
        } else if (warp == 8) {
            ep = __shfl_sync(0xffffffffu, ep, 0) / NCTA + 1;
            while (!(ld_pkt16(pt.mail->mod1 + 256).x & (1 + (ep & 1)))) __nanosleep(200);
        }
        asm volatile("setmaxnreg.dec.sync.aligned.u32 %0;" :: "n"(504 - 2 * RC));

        if (warp == 8 || (warp == 11 && !aux)) {
            const bool act = warp == 11;
            if (act) {
                const uint4* pk = pt.mail->mod1 + grp * 2048 + j * 32 + lane;
                uint4 a[8];
                while (true) {
                    uint32_t t = 1 + (ep & 1);
#pragma unroll
                    for (int i = 0; i < 8; ++i) { a[i] = ld_pkt16(pk + i * 256); t &= a[i].x; }
                    if (__all_sync(0xffffffffu, t != 0)) break;
                }
                uint32_t r[4];
#pragma unroll
                for (int v = 0; v < 2; ++v) {
                    auto sum = [&](uint32_t uint4::*f) { return bf_round((__uint_as_float(a[v].*f) + __uint_as_float(a[2 + v].*f)) + (__uint_as_float(a[4 + v].*f) + __uint_as_float(a[6 + v].*f))) + v; };
                    r[2 * v] = pack2(sum(&uint4::x), sum(&uint4::y)); r[2 * v + 1] = pack2(sum(&uint4::z), sum(&uint4::w));
                }
                sts128(sb + OFF_PAR + lane * 16, r[0], r[1], r[2], r[3]);
                __syncwarp();
                if (el) mbar_arrive(BAR_ONE(sb, EV_PAR));
            }
            {
                const uint32_t split = sg.z >> 20, bytes = (sg.z & 63) << 10;
                const uint32_t dst = split ? (split >= 3 ? 16384 : 8192) + rank * (split == 2 ? 4096 : bytes >> 1) : 0;
                const uint32_t blk = ((sg.z >> 8) & 15) * j + ((sg.z >> 12) & 255) + (split == 3 ? rank : 0);
                if (split == 2) sg.x += rank << 24;
                if (split == 1 || split == 4) sg.y |= rank << (12 + (split >> 2));
                sg.z = dst | blk << 16 | (sg.z & 63) << 24;
            }
            if (!act && !aux) {
#pragma unroll 1
                for (int h = 0; h < 2; ++h) { mbar_wait(BAR_ONE(sb, h ? EV_ST0 : EV_PAR), 0); first_tiles(h ? NB1 : NB0, h ? 5 : NB1); }
            }
            Ring r{0, 1};
#pragma unroll 1
            for (int s = 0; ; ++s) {
                const uint32_t x = __shfl_sync(0xffffffffu, sg.x, s), y = __shfl_sync(0xffffffffu, sg.y, s), z = __shfl_sync(0xffffffffu, sg.z, s), w = __shfl_sync(0xffffffffu, sg.w, s);
                const uint32_t nx = __shfl_sync(0xffffffffu, sg.x, s + 1);
                if (!x) break;
                if (el) { prefetch_map(&mp.ld[nx >> 24]); prefetch_map(&mp.ld[(nx >> 24) + 1]); }
                const CUtensorMap* const tm = &mp.ld[x >> 24];
                const uint32_t n = x & 255, blk = (z >> 16) & 255, bytes = (z >> 24) << 10, cnt = w >> 24, base = sb + (z & 0xFFFF);
                if (x & (F_SKIP << 16)) {
                    r.slot += n;
                    if (r.slot >= NSLOT) { r.slot -= NSLOT; r.par ^= 1; }
                    continue;
                }
                uint32_t kl;
                {
                    const uint32_t a = (y >> 2) & 63, step = (y >> 16) & 255, ch = a + lane * (step >> 5), u = ch >> 1, q = u < 7 ? u : u - 7;
                    kl = (y & 3) == K_PANEL ? (q + (q >= j)) * 128 + (u < 7 ? 0 : 64) + (ch & 1) * 32
                                            : ch * 32 + ((lane * ((x >> 8) & 255)) >> 7) * (y >> 24) * 64 + ((y & 3) == K_OWN ? kown : 0);
                    kl += (y >> 8) & 48;
                }
                uint32_t wrap = NSLOT - ((x >> 16) & F_WRAP);
                auto acquire = [&](uint32_t& st, uint32_t& fb) {
                    mbar_wait(BAR_EMPTY(sb, r.slot), r.par);
                    st = base + r.slot * SLOT; fb = BAR_FULL(sb, r.slot);
                    if (++r.slot == wrap) { r.slot = 0; r.par ^= 1; }
                    wrap = NSLOT;
                };
                uint32_t st, fb;
                if (w & 0xFFFF) { mbar_wait(sb + OFF_BAR + (w & 0xFFF8), w & 1); fence_async_global(); }
                if (act | aux) {
                    const uint32_t* const fl = g_flags + m * 64 + cnt * 16 + ((kl >> 6) & 15);
                    const int row = (x >> 24) == L_X ? m * 64 : m * 128;
                    uint32_t ready = cnt ? 0 : ~0u;
                    auto need = [&](uint32_t i, uint32_t bits) {
                        while (!((ready >> i) & 1)) {
                            uint32_t v; asm volatile("ld.relaxed.gpu.global.u32 %0, [%1];" : "=r"(v) : "l"(fl) : "memory");
                            ready = __ballot_sync(0xffffffffu, ((v + 3 - 3 * ep) & bits) == bits);
                            fence_async_global();
                        }
                    };
                    if (x & (F_EARLY << 16)) {
                        const uint32_t k0 = __shfl_sync(0xffffffffu, kl, 0), k2 = __shfl_sync(0xffffffffu, kl, 2);
#pragma unroll
                        for (int e = 0; e < 3; ++e) mbar_wait(BAR_FULL(sb, e), 0);
#pragma unroll 1
                        for (int g = 1; g >= 0; --g) {
                            ready = 0;
#pragma unroll
                            for (int e = 0; e < 4; ++e) {
                                if (!(e & 1)) need(e, 3 - 2 * g);
                                fb = g ? BAR_FULL(sb, e ? e - 1 : 4) : BAR_ONE(sb, EV_A0 + e);
                                if (el) { mbar_expect_tx(fb, 4096); tma_load4(sb + (e ? e - 1 : 4) * SLOT + g * 4096, tm + 1, (e < 2 ? k0 : k2) + (e & 1) * 32, row + g * 64, 0, fb); }
                            }
                        }
                        if (el) mbar_arrive(BAR_ONE(sb, EV_SEC));
                        r.slot = 3; r.par ^= 1;
                    }
#pragma unroll 1
                    for (uint32_t i = (x >> 17) & 4; i < n; ++i) {
                        const uint32_t k = __shfl_sync(0xffffffffu, kl, i);
                        need(i, 3);
                        acquire(st, fb);
                        if (el) { mbar_expect_tx(fb, bytes); tma_load4(st, tm, aux ? 0 : k, aux ? k : row, aux ? blk : 0, fb); }
                    }
                } else {
                    const bool twice = el && (x & (F_TWICE << 16)), wd = (x >> 24) == L_WD;
                    const uint32_t more = (x >> 25) == L_WG / 2 ? (bytes >> 13) - 1 : 0;
#pragma unroll 1
                    for (uint32_t i = 0; i < n; ++i) {
                        const uint32_t k = __shfl_sync(0xffffffffu, kl, i);
                        acquire(st, fb);
                        if (twice) mbar_arrive(fb);
                        if (el) { mbar_expect_tx(fb, bytes); tma_load5_mc(st, tm, wd ? blk * 64 : 0, wd ? 0 : k, wd ? 0 : blk, (x >> 24) == L_WKV, wd ? k >> 5 : 0, fb); }
                        if (more && el) tma_load5_mc(st + 8192, tm, 0, k, blk + 1, 0, 0, fb);
                        if (more > 1 && el) tma_load5_mc(st + 16384, tm, 0, k, blk + 2, 0, 0, fb);
                    }
                }
            }
        } else if (!aux) {
            const uint32_t w = warp - 9;
            uint32_t bpar = 0;
            auto send = [&](int t) {
                const CUtensorMap* const tm = t ? &mp.os : &mp.h1s;
                const bool ring = t != 1;
                const uint32_t src = sb + (ring ? OFF_OWN : OFF_STG), par = t & 1;
#pragma unroll 1
                for (uint32_t u = w ? 0 : 1; u < (w ? 1 : 3); ++u) {
                    const uint32_t p = u >> 1, g1 = !(ring && u == 1), g0 = u == 0;
                    if (p && ring) mbar_wait_b(BAR_ONE(sb, EV_SEC), t >> 1);
                    const int col = kown + p * 64, row = m * 128 + g0 * 64;
                    const uint32_t back = BAR_ONE(sb, EV_BACK + w), from = src + p * 16384;
                    if (g1 != g0) {
                        mbar_wait_b(BAR_SFULL(sb, 2 + p), par);
                        if (el) { fence_async_smem(); tma_store(tm, col, row + 64, from + 8192); }
                    }
                    mbar_wait_b(BAR_SFULL(sb, 2 * g0 + p), par);
                    if (el) {
                        fence_async_smem();
                        tma_store(tm, col, row, from + g0 * 8192);
                        bulk_commit();
                        mbar_expect_tx(back, 2048);
                        bulk_wait_all();
#pragma unroll
                        for (int i = 0; i < 4; ++i) tma_load(sb + OFF_JUNK, tm + 2, col, row + (i & 1) * 32 + (i >> 1) * (g1 - g0) * 64, back);
                    }
                    __syncwarp();
                    if (p && ring) {
                        mbar_wait_b(BAR_FULL(sb, 5), 0); mbar_wait_b(BAR_ONE(sb, EV_BACK + 1), t >> 1);
                        if (lane < 4) asm volatile("{\n.reg .b32 r;\nmapa.shared::cluster.u32 r, %0, %1;\nmbarrier.arrive.shared::cluster.b64 _, [r];\n}" :: "r"(BAR_EMPTY(sb, 5)), "r"(lane & 1) : "memory");
                    }
                    mbar_wait_b(back, bpar);
                    bpar ^= 1;
                    if (el) asm volatile("red.relaxed.gpu.global.add.u32 [%0], %1;" :: "l"(g_flags + m * 64 + 16 + t * 16 + 2 * j + p), "r"(g1 + 2 - 2 * g0) : "memory");
                }
            };
            auto gate = [&](int vec, int ev) {
                uint2 a, b; uint32_t n = 0;
                const uint2* src = g_mod + vec * 512 + j * 64 + (lane >> 2) * 8 + (lane & 3);
                while (true) {
                    a = ld_pkt(src); b = ld_pkt(src + 4);
                    if (__all_sync(0xffffffffu, a.y == ep && b.y == ep)) break;
                    SPIN_GUARD(n); __nanosleep(300);
                }
                sts128(sb + OFF_TAB + (ev - EV_GA) * 512 + lane * 16, a.x << 16, a.x & 0xFFFF0000u, b.x << 16, b.x & 0xFFFF0000u);
                __syncwarp();
                if (el) mbar_arrive(BAR_ONE(sb, ev));
            };
            if (lane < 6) prefetch_map(lane < 4 ? &mp.h1s + lane : &mp.ld[L_H1 - 4 + lane]);
            auto count = [&](int f) {
                uint32_t v, n = 0;
                while (true) {
                    asm volatile("ld.acquire.gpu.global.u32 %0, [%1];" : "=r"(v) : "l"(g_flags + f) : "memory");
                    if ((int32_t)(v - ep * 8) >= 0) break;
                    SPIN_GUARD(n); __nanosleep(500);
                }
            };
#pragma unroll 1
            for (int t = 0; t < 3; t += 1 + w) {
                send(t);
                if (w == 0) {
                    if (t && el) mbar_arrive(BAR_ONE(sb, t == 1 ? EV_P2 : EV_SENT));
                    if (t == 1 && m > 0) {
#pragma unroll 4
                        for (int i = 0; i < 16; ++i) (g_halo + ((m - 1) * 8 + j) * 512 + lane)[i * 32] = make_uint4(0, 0, 0, 0);
                    }
                } else {
                    gate(t ? 5 : 2, t ? EV_GB : EV_GA);
                    if (t == 0) {
                        count(FL_LN2);
                        const uint4 v = __ldcg((const uint4*)(g_par2 + j * 128) + lane);
                        mbar_wait_b(BAR_SFULL(sb, 2), 1);
                        sts128(sb + OFF_PAR + lane * 16, v.x, v.y, v.z, v.w);
                        __syncwarp();
                        if (el) mbar_arrive(BAR_ONE(sb, EV_P2));
                    }
                }
            }
            if (!w && el) flag_add(g_flags + FL_DONE);
            if (w) {
#pragma unroll 1
                for (int p = 0; p < 3; ++p) {
                    mbar_wait_b(BAR_ONE(sb, EV_HB), p & 1);
                    __nanosleep(RESTH);
                    if (el) asm volatile("red.release.gpu.global.add.u32 [%0], 1;" :: "l"(g_flags + m * 64 + p) : "memory");
                    count(m * 64 + p);
                    if (el) mbar_arrive(BAR_ONE(sb, EV_H + p));
                }
            }
            cluster_arrive_early = true;
            cluster_arrive();
            mbar_wait_b(BAR_SFULL(sb, w * 2), 1);
        }
        __syncwarp();
    }
    if (aux || (wg == 2 && !cluster_arrive_early)) cluster_arrive();
    cluster_wait();
    bulk_wait_read();
    if (tid == 0) {
        if (aux) flag_add(pt.mail->flags + FL_DONE);
    }
}

typedef CUresult (*EncodeFn)(CUtensorMap*, CUtensorMapDataType, cuuint32_t, void*, const cuuint64_t*, const cuuint64_t*, const cuuint32_t*,
                             const cuuint32_t*, CUtensorMapInterleave, CUtensorMapSwizzle, CUtensorMapL2promotion, CUtensorMapFloatOOBfill);

void make_map(EncodeFn fn, CUtensorMap* m, const void* ptr, uint64_t rows, uint64_t cols, uint32_t brows, uint32_t bcols) {
    cuuint64_t dims[2] = {cols, rows}, strides[1] = {cols * 2};
    cuuint32_t box[2] = {bcols, brows}, es[2] = {1, 1};
    fn(m, CU_TENSOR_MAP_DATA_TYPE_BFLOAT16, 2, (void*)ptr, dims, strides, box, es, CU_TENSOR_MAP_INTERLEAVE_NONE,
       bcols == 64 ? CU_TENSOR_MAP_SWIZZLE_128B : bcols == 32 ? CU_TENSOR_MAP_SWIZZLE_64B : CU_TENSOR_MAP_SWIZZLE_NONE,
       bcols == 8 ? CU_TENSOR_MAP_L2_PROMOTION_NONE : CU_TENSOR_MAP_L2_PROMOTION_L2_128B, CU_TENSOR_MAP_FLOAT_OOB_FILL_NONE);
}
struct View { uint64_t dim[5], stride[4]; uint32_t box[5]; };
void make_view(EncodeFn fn, CUtensorMap* m, const void* ptr, uint32_t rank, const View& v) {
    cuuint64_t dims[5], strides[4];
    cuuint32_t box[5], es[5] = {1, 1, 1, 1, 1};
    for (int i = 0; i < 5; ++i) { dims[i] = v.dim[i]; box[i] = v.box[i]; if (i < 4) strides[i] = v.stride[i] * 2; }
    fn(m, CU_TENSOR_MAP_DATA_TYPE_BFLOAT16, rank, (void*)ptr, dims, strides, box, es, CU_TENSOR_MAP_INTERLEAVE_NONE,
       box[0] == 64 ? CU_TENSOR_MAP_SWIZZLE_128B : CU_TENSOR_MAP_SWIZZLE_64B, CU_TENSOR_MAP_L2_PROMOTION_L2_128B, CU_TENSOR_MAP_FLOAT_OOB_FILL_NONE);
}

}

extern "C" void kernel_launch(void* const* d_in, const int* in_sizes, int n_in, void* d_out, int out_size) {
    (void)in_sizes; (void)n_in; (void)out_size;
    void* fnp = nullptr;
    cudaDriverEntryPointQueryResult qr;
    cudaGetDriverEntryPoint("cuTensorMapEncodeTiled", &fnp, cudaEnableDefault, &qr);
    EncodeFn fn = (EncodeFn)fnp;
    void *h1, *o, *hb, *mail, *sched;
    cudaGetSymbolAddress(&h1, g_h1);
    cudaGetSymbolAddress(&mail, g_mail);
    cudaGetSymbolAddress(&o, g_o);
    cudaGetSymbolAddress(&hb, g_hb);
    cudaGetSymbolAddress(&sched, g_sched);
    Maps mp;
    auto wmap = [&](int i, const void* p, uint64_t rows, uint64_t cols, uint64_t sec, uint32_t brows, uint32_t bblk, uint32_t bsec) {
        make_view(fn, &mp.ld[i], p, i == L_WMOD ? 4 : 5, View{{64, rows, cols / sec / 64, sec, 1}, {cols, 64, cols / sec, 64}, {64, brows, bblk, bsec, 1}});
    };
    auto amap = [&](int i, const void* p, uint64_t cols, uint32_t bcols, uint32_t brows = 128) { make_view(fn, &mp.ld[i], p, 4, View{{cols, S_, 1, 1, 1}, {cols, 64, 64, 64}, {bcols, brows, 1, 1, 1}}); };
    wmap(L_WQKV, d_in[1], D_, 3 * D_, 3, 16, 2, 3);
    wmap(L_WKV, d_in[1], D_, 3 * D_, 3, 16, 2, 2);
    wmap(L_WQ, d_in[1], D_, 3 * D_, 3, 64, 1, 1);
    wmap(L_WQ1, d_in[1], D_, 3 * D_, 3, 32, 1, 1);
    wmap(L_WO, d_in[2], D_, D_, 1, 64, 1, 1);
    wmap(L_WG, d_in[4], D_, F_, 1, 32, 1, 1);
    wmap(L_WU, d_in[5], D_, F_, 1, 32, 1, 1);
    make_view(fn, &mp.ld[L_WD], d_in[6], 5, View{{D_, 2, 4, 4, F_ / 32}, {D_, 8 * D_, 2 * D_, 32 * D_}, {64, 2, 4, 4, 2}});
    wmap(L_WMOD, d_in[8], D_, 6 * D_, 1, 64, 4, 1);
    amap(L_H1, h1, D_, 32); amap(L_H1Q, h1, D_, 64); amap(L_O, o, D_, 64); amap(L_H2, o, D_, 32); amap(L_HB, hb, F_, 64);
    amap(L_H1E, h1, D_, 32, 64); amap(L_H2E, o, D_, 32, 64);
    make_view(fn, &mp.ld[L_X], d_in[0], 4, View{{D_, S_ / 2, 2, 1, 1}, {2 * D_, D_, 64, 64}, {64, 64, 2, 1, 1}});
    make_map(fn, &mp.h1s, h1, S_, D_, 64, 64);
    make_map(fn, &mp.os, o, S_, D_, 64, 64);
    make_map(fn, &mp.h1r, h1, S_, D_, 32, 8);
    make_map(fn, &mp.orr, o, S_, D_, 32, 8);
    make_map(fn, &mp.wm, d_in[8], D_, 6 * D_, 64, 64);
    make_map(fn, &mp.x, d_in[0], S_ / 2, 2 * D_, 64, 64);
    make_map(fn, &mp.out, d_out, S_ / 2, 2 * D_, 8, 64);
    cudaFuncSetAttribute(fused_block_kernel, cudaFuncAttributeMaxDynamicSharedMemorySize, SMEM_BYTES);
    cudaLaunchConfig_t cfg = {};
    cfg.gridDim = dim3(NCTA); cfg.blockDim = dim3(384); cfg.dynamicSmemBytes = SMEM_BYTES; cfg.stream = cudaStreamPerThread;
    cudaLaunchAttribute at[1];
    at[0].id = cudaLaunchAttributeClusterDimension; at[0].val.clusterDim.x = 2; at[0].val.clusterDim.y = 1; at[0].val.clusterDim.z = 1;
    cfg.attrs = at; cfg.numAttrs = 1;
    const Ptrs pt{(const __nv_bfloat16*)d_in[7], (Mail*)mail, (__nv_bfloat16*)hb, (const uint4*)sched};
    cudaLaunchKernelEx(&cfg, fused_block_kernel, pt, mp);
}
```

```cpp
#include <cuda_runtime.h>
#include <cuda_bf16.h>
#include <cuda.h>
#include <stdint.h>
#include <stddef.h>

constexpr int LAG = 3;
constexpr int LAGS = 2;
constexpr int LAGW = 4;
constexpr int LAGD = 3;
constexpr int LAGQ = 3;
constexpr int EARLY = 1;
constexpr int NQ = 6;
constexpr int NS = 5;
constexpr int RC = 224;
constexpr int RESTH = 1000;
constexpr int NB0 = 2;
constexpr int NB1 = 3;
constexpr int GW = 4;
constexpr int GD = 2;
constexpr int SWO = 2;
constexpr int QA = 3;

namespace {

constexpr int S_ = 2048, D_ = 1024, F_ = 3584;
constexpr int NCTA = 132;
constexpr int NSLOT = 6;
constexpr uint32_t SLOT = 32768;
constexpr uint32_t OFF_STG = NSLOT * SLOT;
constexpr uint32_t OFF_BAR = OFF_STG + 32768;
constexpr uint32_t OFF_PAR = OFF_BAR + 384;
constexpr uint32_t OFF_TAB = OFF_PAR + 512;
constexpr uint32_t OFF_JUNK = 0u - 1024;
constexpr uint32_t SMEM_BYTES = 1024 + OFF_TAB + 1024;
constexpr int ST_Q = 33, ST_WO = ST_Q + NQ + NS, ST_GU = ST_WO + 16, ST_G1 = ST_GU + 33;
static_assert(ST_GU % (2 * NSLOT) == 0, "");
constexpr uint32_t OFF_OWN = 5 * SLOT;
constexpr uint32_t sweep_order() {
    uint32_t v = 0, n = 0;
    for (uint32_t hi = 0; hi < 2; ++hi)
        for (int i = 0; i < NS; ++i) { const uint32_t t = ST_WO - NS + i, s = t % NSLOT; if ((s >= 4) == hi) v |= (s | (t / NSLOT & 1) << 3) << (4 * n++); }
    return v;
}
constexpr uint32_t SWEEP = sweep_order();

constexpr int FL_DONE = 16 * 64, FL_LN2 = 16 * 64 + 1;

enum { L_WQKV, L_WKV, L_WQ, L_WO, L_WG, L_WU, L_WQ1, L_WD, L_WMOD, L_H1, L_H1E, L_H1Q, L_X, L_O, L_H2, L_H2E, L_HB, L_COUNT };
struct Maps {
    CUtensorMap wm, x, h1s, os, h1r, orr, ld[L_COUNT], out;
};

struct Mail {
    uint32_t flags[16 * 64 + 32];
    uint2 mod[6 * D_ / 2];
    uint4 mod1[8 * 2048];
    uint4 st1[8 * S_ / 2];
    uint32_t par2[D_];
    uint4 halo[128 * 512];
};
struct Ptrs { const __nv_bfloat16* c; Mail* mail; __nv_bfloat16* hb; const uint4* sched; const __nv_bfloat16* x; };

__device__ __align__(128) Mail g_mail;
__device__ __align__(128) __nv_bfloat16 g_h1[S_ * D_];
__device__ __align__(128) __nv_bfloat16 g_o[S_ * D_];
__device__ __align__(128) __nv_bfloat16 g_hb[S_ * F_];

__device__ __forceinline__ uint32_t smem_u32(const void* p) { return (uint32_t)__cvta_generic_to_shared(p); }
__device__ __forceinline__ void mbar_init(uint32_t bar, uint32_t cnt) { asm volatile("mbarrier.init.shared::cta.b64 [%0], %1;" :: "r"(bar), "r"(cnt) : "memory"); }
__device__ __forceinline__ void mbar_expect_tx(uint32_t bar, uint32_t bytes) { asm volatile("mbarrier.arrive.expect_tx.shared::cta.b64 _, [%0], %1;" :: "r"(bar), "r"(bytes) : "memory"); }
__device__ __forceinline__ void mbar_arrive(uint32_t bar) { asm volatile("mbarrier.arrive.shared::cta.b64 _, [%0];" :: "r"(bar) : "memory"); }
__device__ __forceinline__ void mbar_arrive_if0(uint32_t bar, uint32_t z) {
    asm volatile("{\n.reg .pred p;\nsetp.eq.u32 p, %1, 0;\n@p mbarrier.arrive.shared::cta.b64 _, [%0];\n}" :: "r"(bar), "r"(z) : "memory");
}
__device__ __forceinline__ void mbar_wait(uint32_t bar, uint32_t parity) {
    asm volatile("{\n.reg .pred p;\nW_LOOP:\nmbarrier.try_wait.parity.shared::cta.b64 p, [%0], %1;\n@!p bra W_LOOP;\n}" :: "r"(bar), "r"(parity) : "memory");
}
__device__ __forceinline__ void mbar_wait_b(uint32_t bar, uint32_t parity) {
    asm volatile("{\n.reg .pred p;\n.reg .u32 n;\nmov.u32 n, 0;\n"
        "W_LOOP:\nmbarrier.try_wait.parity.shared::cta.b64 p, [%0], %1;\n@p bra W_DONE;\n"
        "add.u32 n, n, 1;\nsetp.lt.u32 p, n, 0x400000;\n@p bra W_LOOP;\ntrap;\nW_DONE:\n}" :: "r"(bar), "r"(parity) : "memory");
}
__device__ __forceinline__ void tma_load(uint32_t dst, const CUtensorMap* m, int c0, int c1, uint32_t bar) {
    asm volatile("cp.async.bulk.tensor.2d.shared::cluster.global.mbarrier::complete_tx::bytes [%0], [%1, {%3, %4}], [%2];"
        :: "r"(dst), "l"(m), "r"(bar), "r"(c0), "r"(c1) : "memory");
}
__device__ __forceinline__ void tma_load4(uint32_t dst, const CUtensorMap* m, int c0, int c1, int c2, uint32_t bar) {
    asm volatile("cp.async.bulk.tensor.4d.shared::cluster.global.mbarrier::complete_tx::bytes [%0], [%1, {%3, %4, %5, %6}], [%2];"
        :: "r"(dst), "l"(m), "r"(bar), "r"(c0), "r"(c1), "r"(c2), "r"(0) : "memory");
}
__device__ __forceinline__ void tma_load5_mc(uint32_t dst, const CUtensorMap* m, int c0, int c1, int c2, int c3, int c4, uint32_t bar) {
    asm volatile("cp.async.bulk.tensor.5d.shared::cluster.global.mbarrier::complete_tx::bytes.multicast::cluster.L2::cache_hint [%0], [%1, {%3, %4, %5, %6, %7}], [%2], %8, %9;"
        :: "r"(dst), "l"(m), "r"(bar), "r"(c0), "r"(c1), "r"(c2), "r"(c3), "r"(c4), "h"((uint16_t)3), "l"(0x12F0000000000000ull) : "memory");
}
__device__ __forceinline__ void tma_store(const CUtensorMap* m, int c0, int c1, uint32_t src) {
    asm volatile("cp.async.bulk.tensor.2d.global.shared::cta.bulk_group [%0, {%2, %3}], [%1];" :: "l"(m), "r"(src), "r"(c0), "r"(c1) : "memory");
}
__device__ __forceinline__ void bulk_commit() { asm volatile("cp.async.bulk.commit_group;" ::: "memory"); }
__device__ __forceinline__ void bulk_wait_read() { asm volatile("cp.async.bulk.wait_group.read 0;" ::: "memory"); }
__device__ __forceinline__ void bulk_wait_all() { asm volatile("cp.async.bulk.wait_group 0;" ::: "memory"); }
__device__ __forceinline__ void fence_async_smem() { asm volatile("fence.proxy.async.shared::cta;" ::: "memory"); }
__device__ __forceinline__ void fence_async_global() { asm volatile("fence.proxy.async.global;" ::: "memory"); }
__device__ __forceinline__ void prefetch_map(const CUtensorMap* m) { asm volatile("prefetch.tensormap [%0];" :: "l"(m) : "memory"); }
__device__ __forceinline__ void wg_fence() { asm volatile("wgmma.fence.sync.aligned;" ::: "memory"); }
__device__ __forceinline__ void wg_commit() { asm volatile("wgmma.commit_group.sync.aligned;" ::: "memory"); }
template <int N> __device__ __forceinline__ void wg_wait() { asm volatile("wgmma.wait_group.sync.aligned %0;" :: "n"(N) : "memory"); }
__device__ __forceinline__ void bar_sync(int id, int n) { asm volatile("bar.sync %0, %1;" :: "r"(id), "r"(n) : "memory"); }
__device__ __forceinline__ void flag_add(uint32_t* f) { asm volatile("red.relaxed.gpu.global.add.u32 [%0], 1;" :: "l"(f) : "memory"); }
__device__ __forceinline__ uint32_t d16(uint32_t addr) { return (addr & 0x3FFFF) >> 4; }
__device__ __forceinline__ uint64_t mk_desc(uint32_t a16, uint32_t off, uint32_t lbo, uint32_t sbo, uint32_t swz) {
    const uint32_t lo = a16 + (off >> 4) + ((lbo >> 4) << 16), hi = (sbo >> 4) | (swz << 30);
    return ((uint64_t)hi << 32) | lo;
}
__device__ __forceinline__ uint32_t pack2(float lo, float hi) {
    uint32_t r; asm("cvt.rn.bf16x2.f32 %0, %1, %2;" : "=r"(r) : "f"(hi), "f"(lo)); return r;
}
__device__ __forceinline__ uint32_t hfma2_bf16(uint32_t a, uint32_t b, uint32_t c) {
    uint32_t r; asm("fma.rn.bf16x2 %0, %1, %2, %3;" : "=r"(r) : "r"(a), "r"(b), "r"(c)); return r;
}
__device__ __forceinline__ float bf_lo(uint32_t v) { return __uint_as_float(v << 16); }
__device__ __forceinline__ float bf_hi(uint32_t v) { return __uint_as_float(v & 0xFFFF0000u); }
__device__ __forceinline__ float bf_round(float x) { return __bfloat162float(__float2bfloat16_rn(x)); }
__device__ __forceinline__ void stsm4(uint32_t addr, uint32_t r0, uint32_t r1, uint32_t r2, uint32_t r3) {
    asm volatile("stmatrix.sync.aligned.m8n8.x4.shared.b16 [%0], {%1, %2, %3, %4};" :: "r"(addr), "r"(r0), "r"(r1), "r"(r2), "r"(r3) : "memory");
}
__device__ __forceinline__ void stsm4t(uint32_t addr, uint32_t r0, uint32_t r1, uint32_t r2, uint32_t r3) {
    asm volatile("stmatrix.sync.aligned.m8n8.x4.trans.shared.b16 [%0], {%1, %2, %3, %4};" :: "r"(addr), "r"(r0), "r"(r1), "r"(r2), "r"(r3) : "memory");
}
__device__ __forceinline__ void ldsm4(uint32_t addr, uint32_t& r0, uint32_t& r1, uint32_t& r2, uint32_t& r3) {
    asm volatile("ldmatrix.sync.aligned.m8n8.x4.shared.b16 {%0, %1, %2, %3}, [%4];" : "=r"(r0), "=r"(r1), "=r"(r2), "=r"(r3) : "r"(addr) : "memory");
}
__device__ __forceinline__ uint32_t movm(uint32_t a) { uint32_t r; asm volatile("movmatrix.sync.aligned.m8n8.trans.b16 %0, %1;" : "=r"(r) : "r"(a)); return r; }
__device__ __forceinline__ void mma16816(float (&c)[4], uint32_t a0, uint32_t a1, uint32_t a2, uint32_t a3, uint32_t b0, uint32_t b1) {
    asm("mma.sync.aligned.m16n8k16.row.col.f32.bf16.bf16.f32 {%0, %1, %2, %3}, {%4, %5, %6, %7}, {%8, %9}, {%0, %1, %2, %3};"
        : "+f"(c[0]), "+f"(c[1]), "+f"(c[2]), "+f"(c[3]) : "r"(a0), "r"(a1), "r"(a2), "r"(a3), "r"(b0), "r"(b1));
}
__device__ __forceinline__ float ex2(float x) { float r; asm("ex2.approx.ftz.f32 %0, %1;" : "=f"(r) : "f"(x)); return r; }
__device__ __forceinline__ float rcp(float x) { float r; asm("rcp.approx.ftz.f32 %0, %1;" : "=f"(r) : "f"(x)); return r; }
__device__ __forceinline__ float rsq(float x) { float r; asm("rsqrt.approx.ftz.f32 %0, %1;" : "=f"(r) : "f"(x)); return r; }
__device__ __forceinline__ float silu_(float x) { return x * rcp(1.f + ex2(-1.4426950408889634f * x)); }
__device__ __forceinline__ void st_pkt(void* p, uint32_t a, uint32_t b) {
    asm volatile("{\n.reg .b64 t;\nmov.b64 t, {%1, %2};\nst.relaxed.gpu.global.b64 [%0], t;\n}" :: "l"(p), "r"(a), "r"(b) : "memory");
}
__device__ __forceinline__ uint2 ld_pkt(const void* p) {
    uint2 v; asm volatile("{\n.reg .b64 t;\nld.relaxed.gpu.global.b64 t, [%2];\nmov.b64 {%0, %1}, t;\n}" : "=r"(v.x), "=r"(v.y) : "l"(p) : "memory"); return v;
}
__device__ __forceinline__ void st_pkt16(void* p, uint32_t a, uint32_t b, uint32_t c, uint32_t d) {
    asm volatile("{\n.reg .b64 t, u;\n.reg .b128 w;\nmov.b64 t, {%1, %2};\nmov.b64 u, {%3, %4};\nmov.b128 w, {t, u};\nst.relaxed.gpu.global.b128 [%0], w;\n}"
        :: "l"(p), "r"(a), "r"(b), "r"(c), "r"(d) : "memory");
}
__device__ __forceinline__ uint4 ld_pkt16(const void* p) {
    uint4 v; asm volatile("{\n.reg .b64 t, u;\n.reg .b128 w;\nld.relaxed.gpu.global.b128 w, [%4];\nmov.b128 {t, u}, w;\nmov.b64 {%0, %1}, t;\nmov.b64 {%2, %3}, u;\n}"
        : "=r"(v.x), "=r"(v.y), "=r"(v.z), "=r"(v.w) : "l"(p) : "memory"); return v;
}
#define SPIN_GUARD(n) do { if (++(n) > (1u << 22)) asm volatile("trap;"); } while (0)
__device__ __forceinline__ uint4 lds128(uint32_t a) { uint4 v; asm volatile("ld.shared.v4.u32 {%0, %1, %2, %3}, [%4];" : "=r"(v.x), "=r"(v.y), "=r"(v.z), "=r"(v.w) : "r"(a) : "memory"); return v; }
__device__ __forceinline__ void sts128(uint32_t a, uint32_t x, uint32_t y, uint32_t z, uint32_t w) { asm volatile("st.shared.v4.u32 [%0], {%1, %2, %3, %4};" :: "r"(a), "r"(x), "r"(y), "r"(z), "r"(w) : "memory"); }
__device__ __forceinline__ uint2 lds64(uint32_t a) { uint2 v; asm volatile("ld.shared.v2.u32 {%0, %1}, [%2];" : "=r"(v.x), "=r"(v.y) : "r"(a) : "memory"); return v; }
__device__ __forceinline__ void sts64(uint32_t a, uint32_t x, uint32_t y) { asm volatile("st.shared.v2.u32 [%0], {%1, %2};" :: "r"(a), "r"(x), "r"(y) : "memory"); }
__device__ __forceinline__ uint32_t lds32(uint32_t a) { uint32_t v; asm volatile("ld.shared.u32 %0, [%1];" : "=r"(v) : "r"(a) : "memory"); return v; }
__device__ __forceinline__ void sts32(uint32_t a, uint32_t v) { asm volatile("st.shared.u32 [%0], %1;" :: "r"(a), "r"(v) : "memory"); }
__device__ __forceinline__ bool elect_one() {
    uint32_t p; asm volatile("{\n.reg .pred q;\nelect.sync _|q, 0xffffffff;\nselp.u32 %0, 1, 0, q;\n}" : "=r"(p)); return p;
}
__device__ __forceinline__ void cluster_arrive() { asm volatile("barrier.cluster.arrive.relaxed.aligned;" ::: "memory"); }
__device__ __forceinline__ void cluster_wait() { asm volatile("barrier.cluster.wait.aligned;" ::: "memory"); }

__device__ __forceinline__ void wgmma_n128_z(float (&d)[64], uint64_t da, uint64_t db) {
    asm volatile("{\n.reg .pred p;\nsetp.ne.b32 p, 0, 0;\n"
        "wgmma.mma_async.sync.aligned.m64n128k16.f32.bf16.bf16 {"
        "%0, %1, %2, %3, %4, %5, %6, %7, %8, %9, %10, %11, %12, %13, %14, %15, "
        "%16, %17, %18, %19, %20, %21, %22, %23, %24, %25, %26, %27, %28, %29, %30, %31, "
        "%32, %33, %34, %35, %36, %37, %38, %39, %40, %41, %42, %43, %44, %45, %46, %47, "
        "%48, %49, %50, %51, %52, %53, %54, %55, %56, %57, %58, %59, %60, %61, %62, %63"
        "}, %64, %65, p, 1, 1, 0, 1;\n}\n"
        : "=f"(d[0]), "=f"(d[1]), "=f"(d[2]), "=f"(d[3]), "=f"(d[4]), "=f"(d[5]), "=f"(d[6]), "=f"(d[7]),
          "=f"(d[8]), "=f"(d[9]), "=f"(d[10]), "=f"(d[11]), "=f"(d[12]), "=f"(d[13]), "=f"(d[14]), "=f"(d[15]),
          "=f"(d[16]), "=f"(d[17]), "=f"(d[18]), "=f"(d[19]), "=f"(d[20]), "=f"(d[21]), "=f"(d[22]), "=f"(d[23]),
          "=f"(d[24]), "=f"(d[25]), "=f"(d[26]), "=f"(d[27]), "=f"(d[28]), "=f"(d[29]), "=f"(d[30]), "=f"(d[31]),
          "=f"(d[32]), "=f"(d[33]), "=f"(d[34]), "=f"(d[35]), "=f"(d[36]), "=f"(d[37]), "=f"(d[38]), "=f"(d[39]),
          "=f"(d[40]), "=f"(d[41]), "=f"(d[42]), "=f"(d[43]), "=f"(d[44]), "=f"(d[45]), "=f"(d[46]), "=f"(d[47]),
          "=f"(d[48]), "=f"(d[49]), "=f"(d[50]), "=f"(d[51]), "=f"(d[52]), "=f"(d[53]), "=f"(d[54]), "=f"(d[55]),
          "=f"(d[56]), "=f"(d[57]), "=f"(d[58]), "=f"(d[59]), "=f"(d[60]), "=f"(d[61]), "=f"(d[62]), "=f"(d[63])
        : "l"(da), "l"(db));
}
__device__ __forceinline__ void wgmma_n128(float (&d)[64], uint64_t da, uint64_t db) {
    asm volatile("{\n.reg .pred p;\nsetp.eq.b32 p, 0, 0;\n"
        "wgmma.mma_async.sync.aligned.m64n128k16.f32.bf16.bf16 {"
        "%0, %1, %2, %3, %4, %5, %6, %7, %8, %9, %10, %11, %12, %13, %14, %15, "
        "%16, %17, %18, %19, %20, %21, %22, %23, %24, %25, %26, %27, %28, %29, %30, %31, "
        "%32, %33, %34, %35, %36, %37, %38, %39, %40, %41, %42, %43, %44, %45, %46, %47, "
        "%48, %49, %50, %51, %52, %53, %54, %55, %56, %57, %58, %59, %60, %61, %62, %63"
        "}, %64, %65, p, 1, 1, 0, 1;\n}\n"
        : "+f"(d[0]), "+f"(d[1]), "+f"(d[2]), "+f"(d[3]), "+f"(d[4]), "+f"(d[5]), "+f"(d[6]), "+f"(d[7]),
          "+f"(d[8]), "+f"(d[9]), "+f"(d[10]), "+f"(d[11]), "+f"(d[12]), "+f"(d[13]), "+f"(d[14]), "+f"(d[15]),
          "+f"(d[16]), "+f"(d[17]), "+f"(d[18]), "+f"(d[19]), "+f"(d[20]), "+f"(d[21]), "+f"(d[22]), "+f"(d[23]),
          "+f"(d[24]), "+f"(d[25]), "+f"(d[26]), "+f"(d[27]), "+f"(d[28]), "+f"(d[29]), "+f"(d[30]), "+f"(d[31]),
          "+f"(d[32]), "+f"(d[33]), "+f"(d[34]), "+f"(d[35]), "+f"(d[36]), "+f"(d[37]), "+f"(d[38]), "+f"(d[39]),
          "+f"(d[40]), "+f"(d[41]), "+f"(d[42]), "+f"(d[43]), "+f"(d[44]), "+f"(d[45]), "+f"(d[46]), "+f"(d[47]),
          "+f"(d[48]), "+f"(d[49]), "+f"(d[50]), "+f"(d[51]), "+f"(d[52]), "+f"(d[53]), "+f"(d[54]), "+f"(d[55]),
          "+f"(d[56]), "+f"(d[57]), "+f"(d[58]), "+f"(d[59]), "+f"(d[60]), "+f"(d[61]), "+f"(d[62]), "+f"(d[63])
        : "l"(da), "l"(db));
}
__device__ __forceinline__ void wgmma_n256_z(float (&d)[128], uint64_t da, uint64_t db) {
    asm volatile("{\n.reg .pred p;\nsetp.ne.b32 p, 0, 0;\n"
        "wgmma.mma_async.sync.aligned.m64n256k16.f32.bf16.bf16 {"
        "%0, %1, %2, %3, %4, %5, %6, %7, %8, %9, %10, %11, %12, %13, %14, %15, "
        "%16, %17, %18, %19, %20, %21, %22, %23, %24, %25, %26, %27, %28, %29, %30, %31, "
        "%32, %33, %34, %35, %36, %37, %38, %39, %40, %41, %42, %43, %44, %45, %46, %47, "
        "%48, %49, %50, %51, %52, %53, %54, %55, %56, %57, %58, %59, %60, %61, %62, %63, "
        "%64, %65, %66, %67, %68, %69, %70, %71, %72, %73, %74, %75, %76, %77, %78, %79, "
        "%80, %81, %82, %83, %84, %85, %86, %87, %88, %89, %90, %91, %92, %93, %94, %95, "
        "%96, %97, %98, %99, %100, %101, %102, %103, %104, %105, %106, %107, %108, %109, %110, %111, "
        "%112, %113, %114, %115, %116, %117, %118, %119, %120, %121, %122, %123, %124, %125, %126, %127"
        "}, %128, %129, p, 1, 1, 0, 1;\n}\n"
        : "=f"(d[0]), "=f"(d[1]), "=f"(d[2]), "=f"(d[3]), "=f"(d[4]), "=f"(d[5]), "=f"(d[6]), "=f"(d[7]),
          "=f"(d[8]), "=f"(d[9]), "=f"(d[10]), "=f"(d[11]), "=f"(d[12]), "=f"(d[13]), "=f"(d[14]), "=f"(d[15]),
          "=f"(d[16]), "=f"(d[17]), "=f"(d[18]), "=f"(d[19]), "=f"(d[20]), "=f"(d[21]), "=f"(d[22]), "=f"(d[23]),
          "=f"(d[24]), "=f"(d[25]), "=f"(d[26]), "=f"(d[27]), "=f"(d[28]), "=f"(d[29]), "=f"(d[30]), "=f"(d[31]),
          "=f"(d[32]), "=f"(d[33]), "=f"(d[34]), "=f"(d[35]), "=f"(d[36]), "=f"(d[37]), "=f"(d[38]), "=f"(d[39]),
          "=f"(d[40]), "=f"(d[41]), "=f"(d[42]), "=f"(d[43]), "=f"(d[44]), "=f"(d[45]), "=f"(d[46]), "=f"(d[47]),
          "=f"(d[48]), "=f"(d[49]), "=f"(d[50]), "=f"(d[51]), "=f"(d[52]), "=f"(d[53]), "=f"(d[54]), "=f"(d[55]),
          "=f"(d[56]), "=f"(d[57]), "=f"(d[58]), "=f"(d[59]), "=f"(d[60]), "=f"(d[61]), "=f"(d[62]), "=f"(d[63]),
          "=f"(d[64]), "=f"(d[65]), "=f"(d[66]), "=f"(d[67]), "=f"(d[68]), "=f"(d[69]), "=f"(d[70]), "=f"(d[71]),
          "=f"(d[72]), "=f"(d[73]), "=f"(d[74]), "=f"(d[75]), "=f"(d[76]), "=f"(d[77]), "=f"(d[78]), "=f"(d[79]),
          "=f"(d[80]), "=f"(d[81]), "=f"(d[82]), "=f"(d[83]), "=f"(d[84]), "=f"(d[85]), "=f"(d[86]), "=f"(d[87]),
          "=f"(d[88]), "=f"(d[89]), "=f"(d[90]), "=f"(d[91]), "=f"(d[92]), "=f"(d[93]), "=f"(d[94]), "=f"(d[95]),
          "=f"(d[96]), "=f"(d[97]), "=f"(d[98]), "=f"(d[99]), "=f"(d[100]), "=f"(d[101]), "=f"(d[102]), "=f"(d[103]),
          "=f"(d[104]), "=f"(d[105]), "=f"(d[106]), "=f"(d[107]), "=f"(d[108]), "=f"(d[109]), "=f"(d[110]), "=f"(d[111]),
          "=f"(d[112]), "=f"(d[113]), "=f"(d[114]), "=f"(d[115]), "=f"(d[116]), "=f"(d[117]), "=f"(d[118]), "=f"(d[119]),
          "=f"(d[120]), "=f"(d[121]), "=f"(d[122]), "=f"(d[123]), "=f"(d[124]), "=f"(d[125]), "=f"(d[126]), "=f"(d[127])
        : "l"(da), "l"(db));
}
__device__ __forceinline__ void wgmma_n256(float (&d)[128], uint64_t da, uint64_t db) {
    asm volatile("{\n.reg .pred p;\nsetp.eq.b32 p, 0, 0;\n"
        "wgmma.mma_async.sync.aligned.m64n256k16.f32.bf16.bf16 {"
        "%0, %1, %2, %3, %4, %5, %6, %7, %8, %9, %10, %11, %12, %13, %14, %15, "
        "%16, %17, %18, %19, %20, %21, %22, %23, %24, %25, %26, %27, %28, %29, %30, %31, "
        "%32, %33, %34, %35, %36, %37, %38, %39, %40, %41, %42, %43, %44, %45, %46, %47, "
        "%48, %49, %50, %51, %52, %53, %54, %55, %56, %57, %58, %59, %60, %61, %62, %63, "
        "%64, %65, %66, %67, %68, %69, %70, %71, %72, %73, %74, %75, %76, %77, %78, %79, "
        "%80, %81, %82, %83, %84, %85, %86, %87, %88, %89, %90, %91, %92, %93, %94, %95, "
        "%96, %97, %98, %99, %100, %101, %102, %103, %104, %105, %106, %107, %108, %109, %110, %111, "
        "%112, %113, %114, %115, %116, %117, %118, %119, %120, %121, %122, %123, %124, %125, %126, %127"
        "}, %128, %129, p, 1, 1, 0, 1;\n}\n"
        : "+f"(d[0]), "+f"(d[1]), "+f"(d[2]), "+f"(d[3]), "+f"(d[4]), "+f"(d[5]), "+f"(d[6]), "+f"(d[7]),
          "+f"(d[8]), "+f"(d[9]), "+f"(d[10]), "+f"(d[11]), "+f"(d[12]), "+f"(d[13]), "+f"(d[14]), "+f"(d[15]),
          "+f"(d[16]), "+f"(d[17]), "+f"(d[18]), "+f"(d[19]), "+f"(d[20]), "+f"(d[21]), "+f"(d[22]), "+f"(d[23]),
          "+f"(d[24]), "+f"(d[25]), "+f"(d[26]), "+f"(d[27]), "+f"(d[28]), "+f"(d[29]), "+f"(d[30]), "+f"(d[31]),
          "+f"(d[32]), "+f"(d[33]), "+f"(d[34]), "+f"(d[35]), "+f"(d[36]), "+f"(d[37]), "+f"(d[38]), "+f"(d[39]),
          "+f"(d[40]), "+f"(d[41]), "+f"(d[42]), "+f"(d[43]), "+f"(d[44]), "+f"(d[45]), "+f"(d[46]), "+f"(d[47]),
          "+f"(d[48]), "+f"(d[49]), "+f"(d[50]), "+f"(d[51]), "+f"(d[52]), "+f"(d[53]), "+f"(d[54]), "+f"(d[55]),
          "+f"(d[56]), "+f"(d[57]), "+f"(d[58]), "+f"(d[59]), "+f"(d[60]), "+f"(d[61]), "+f"(d[62]), "+f"(d[63]),
          "+f"(d[64]), "+f"(d[65]), "+f"(d[66]), "+f"(d[67]), "+f"(d[68]), "+f"(d[69]), "+f"(d[70]), "+f"(d[71]),
          "+f"(d[72]), "+f"(d[73]), "+f"(d[74]), "+f"(d[75]), "+f"(d[76]), "+f"(d[77]), "+f"(d[78]), "+f"(d[79]),
          "+f"(d[80]), "+f"(d[81]), "+f"(d[82]), "+f"(d[83]), "+f"(d[84]), "+f"(d[85]), "+f"(d[86]), "+f"(d[87]),
          "+f"(d[88]), "+f"(d[89]), "+f"(d[90]), "+f"(d[91]), "+f"(d[92]), "+f"(d[93]), "+f"(d[94]), "+f"(d[95]),
          "+f"(d[96]), "+f"(d[97]), "+f"(d[98]), "+f"(d[99]), "+f"(d[100]), "+f"(d[101]), "+f"(d[102]), "+f"(d[103]),
          "+f"(d[104]), "+f"(d[105]), "+f"(d[106]), "+f"(d[107]), "+f"(d[108]), "+f"(d[109]), "+f"(d[110]), "+f"(d[111]),
          "+f"(d[112]), "+f"(d[113]), "+f"(d[114]), "+f"(d[115]), "+f"(d[116]), "+f"(d[117]), "+f"(d[118]), "+f"(d[119]),
          "+f"(d[120]), "+f"(d[121]), "+f"(d[122]), "+f"(d[123]), "+f"(d[124]), "+f"(d[125]), "+f"(d[126]), "+f"(d[127])
        : "l"(da), "l"(db));
}
template <int O, int L>
__device__ __forceinline__ void wgmma_n64(float (&d)[L], uint64_t da, uint64_t db) {
    asm volatile("{\n.reg .pred p;\nsetp.eq.b32 p, 0, 0;\n"
        "wgmma.mma_async.sync.aligned.m64n64k16.f32.bf16.bf16 {%0, %1, %2, %3, %4, %5, %6, %7, %8, %9, %10, %11, %12, %13, %14, %15, %16, %17, %18, %19, %20, %21, %22, %23, %24, %25, %26, %27, %28, %29, %30, %31}, %32, %33, p, 1, 1, 0, 1;\n}\n"
        : "+f"(d[O + 0]), "+f"(d[O + 1]), "+f"(d[O + 2]), "+f"(d[O + 3]), "+f"(d[O + 4]), "+f"(d[O + 5]), "+f"(d[O + 6]), "+f"(d[O + 7]),
          "+f"(d[O + 8]), "+f"(d[O + 9]), "+f"(d[O + 10]), "+f"(d[O + 11]), "+f"(d[O + 12]), "+f"(d[O + 13]), "+f"(d[O + 14]), "+f"(d[O + 15]),
          "+f"(d[O + 16]), "+f"(d[O + 17]), "+f"(d[O + 18]), "+f"(d[O + 19]), "+f"(d[O + 20]), "+f"(d[O + 21]), "+f"(d[O + 22]), "+f"(d[O + 23]),
          "+f"(d[O + 24]), "+f"(d[O + 25]), "+f"(d[O + 26]), "+f"(d[O + 27]), "+f"(d[O + 28]), "+f"(d[O + 29]), "+f"(d[O + 30]), "+f"(d[O + 31])
        : "l"(da), "l"(db));
}


struct Idx {
    uint32_t lane, warp, w4, q4, g8, prow, pan;
    __device__ __forceinline__ Idx() {
        uint32_t t; asm volatile("mov.u32 %0, %%tid.x;" : "=r"(t));
        lane = t & 31; warp = t >> 5; w4 = warp & 3; q4 = lane & 3; g8 = lane >> 2;
        prow = w4 * 16 + ((lane >> 3) & 1) * 8 + (lane & 7);
        pan = prow * 128 + (((lane >> 4) ^ (lane & 7)) << 4);
    }
};
#define IDX() const Idx ix; const uint32_t lane = ix.lane, warp = ix.warp, w4 = ix.w4, q4 = ix.q4, g8 = ix.g8, prow = ix.prow, pan_addr = ix.pan; \
    (void)lane; (void)warp; (void)w4; (void)q4; (void)g8; (void)prow; (void)pan_addr;

struct Ring {
    uint32_t slot, par;
    __device__ __forceinline__ void next() { if (++slot == NSLOT) { slot = 0; par ^= 1; } }
};
__device__ __forceinline__ uint32_t BAR_FULL(uint32_t sb, uint32_t s) { return sb + OFF_BAR + 8 * s; }
__device__ __forceinline__ uint32_t BAR_EMPTY(uint32_t sb, uint32_t s) { return sb + OFF_BAR + 48 + 8 * s; }
__device__ __forceinline__ uint32_t BAR_SFULL(uint32_t sb, uint32_t i) { return sb + OFF_BAR + 96 + 8 * i; }
__device__ __forceinline__ uint32_t BAR_ONE(uint32_t sb, uint32_t i) { return sb + OFF_BAR + 128 + 8 * i; }
enum { EV_X1, EV_WIN, EV_WINL = EV_WIN + 3, EV_X, EV_ST0, EV_GA, EV_GB, EV_P2, EV_LAG0, EV_LAG1, EV_LAG2, EV_LAG3, EV_LAG4, EV_LAG5, EV_HB, EV_H, EV_H1, EV_H2, EV_SENT, EV_SEC, EV_BACK, EV_BACK1, EV_A0, EV_A0L = EV_A0 + 3, EV_PAR, EV_COUNT };

static_assert(128 + 8 * EV_COUNT <= 384, "");

enum { K_ABS, K_OWN, K_PANEL };
enum { F_WRAP = 1, F_TWICE = 2, F_SKIP = 4, F_EARLY = 8 };
constexpr uint32_t pre_ev(uint32_t ev) { return 128 + 8 * ev; }
constexpr uint32_t pre_sfull(uint32_t i, uint32_t par) { return 96 + 8 * i + par; }
constexpr uint4 seg(uint32_t n, uint32_t kind, uint32_t a, uint32_t step, uint32_t q, uint32_t jump, uint32_t flags, uint32_t map, uint32_t kb, uint32_t pre = 0,
                    uint32_t blkj = 0, uint32_t blk = 0, uint32_t split = 0, uint32_t cnt = 0) {
    return uint4{n | (127 + q) / q << 8 | flags << 16 | map << 24, kind | a << 2 | step << 16 | jump / 64 << 24, kb | blkj << 8 | blk << 12 | split << 20, pre | cnt << 24};
}
constexpr int NSEG = 14;
__device__ const uint4 g_sched[3][NSEG] = {
    {seg(NSLOT, K_ABS, 0, 0, 1, 0, F_SKIP, L_WQKV, 0),
     seg(27 - 2 * NQ, K_PANEL, 1, 32, 2, 64, 0, L_WQKV, 24, 0, 2, 0, 1), seg(2 * NQ, K_PANEL, 28 - 2 * NQ, 32, 2, 64, 0, L_WKV, 16, 0, 2, 0, 1),
     seg(NQ, K_PANEL, 28 - 2 * NQ, 64, 1, 64, 0, L_WQ, 16, 0, 2, 0, 3), seg(NS, K_PANEL, 28 - 2 * NQ - 2 * NS, 64, 1, 64, 0, L_WQ1, 8, 0, 2, 1, 4),
     seg(2, K_OWN, 0, 64, 32, 0, 0, L_WO, 16, 0, 2, 0, 3), seg(14, K_PANEL, 0, 64, 1, 64, 0, L_WO, 16, 0, 2, 0, 3),
     seg(4, K_OWN, 0, 32, 32, 0, F_TWICE, L_WG, 24, 0, 7, 0, 2), seg(28, K_PANEL, 0, 32, 2, 64, F_WRAP, L_WG, 24, 0, 7, 0, 2),
     seg(32, K_ABS, 0, 32, 32, 0, 0, L_WG, 16, 0, 7, 3, 2), seg(32, K_ABS, 0, 32, 32, 0, 0, L_WG, 16, 0, 7, 5, 2),
     seg(24, K_ABS, 0, 64, 3, 256, 0, L_WD, 16, 0, 2, 0, 3), seg(16, K_ABS, 6, 64, 2, 320, 0, L_WD, 16, 0, 2, 0, 3), seg(16, K_ABS, 10, 64, 2, 320, 0, L_WD, 16, 0, 2, 0, 3)},
    {seg(28, K_PANEL, 0, 32, 2, 64, F_EARLY, L_H1, 8, pre_sfull(2, 0), 0, 0, 0, 1),
     seg(NQ, K_PANEL, 28 - 2 * NQ, 64, 1, 64, 0, L_H1Q, 16), seg(NS, K_PANEL, 28 - 2 * NQ - 2 * NS, 64, 1, 64, 0, L_H1Q, 16),
     seg(2, K_OWN, 0, 64, 32, 0, 0, L_X, 16), seg(14, K_PANEL, 0, 64, 1, 64, 0, L_O, 16, pre_sfull(0, 1), 0, 0, 0, 2),
     seg(28, K_PANEL, 0, 32, 2, 64, F_EARLY, L_H2, 8, pre_sfull(2, 0), 0, 0, 0, 3),
     seg(32, K_ABS, 0, 32, 32, 0, 0, L_H2, 8, pre_ev(EV_SENT)), seg(32, K_ABS, 0, 32, 32, 0, 0, L_H2, 8),
     seg(24, K_ABS, 0, 64, 3, 256, 0, L_HB, 16, pre_ev(EV_H)), seg(16, K_ABS, 6, 64, 2, 320, 0, L_HB, 16, pre_ev(EV_H1)), seg(16, K_ABS, 10, 64, 2, 320, 0, L_HB, 16, pre_ev(EV_H2))},
    {seg(16, K_ABS, 0, 64, 32, 0, 0, L_WMOD, 32, 0, 4, 32), seg(16, K_ABS, 0, 64, 32, 0, 0, L_WMOD, 32, 0, 4, 48),
     seg(16, K_ABS, 0, 64, 32, 0, 0, L_WMOD, 32, 0, 4, 64), seg(16, K_ABS, 0, 64, 32, 0, 0, L_WMOD, 32, 0, 4, 80)}};

struct Pipe {
    uint32_t sb, slot, par, tok, rel;
    __device__ __forceinline__ void arm() {
        uint32_t t, a; asm volatile("mov.u32 %0, %%tid.x;" : "=r"(t));
        asm("mapa.shared::cluster.u32 %0, %1, %2;" : "=r"(a) : "r"(BAR_EMPTY(sb, 0)), "r"((t >> 5) & 1));
        tok = __shfl_sync(0xffffffffu, (t & 95u) == 0 ? a : 0, t & 31);
    }
    __device__ __forceinline__ uint32_t stage() {
        mbar_wait(BAR_FULL(sb, slot), par);
        return d16(sb) + slot * (SLOT >> 4);
    }
    __device__ __forceinline__ void release() { if (rel) asm volatile("mbarrier.arrive.shared::cluster.b64 _, [%0];" :: "r"(rel) : "memory"); rel = 0; }
    __device__ __forceinline__ void issued() {
        wg_commit(); wg_wait<1>(); release();
        if (tok) rel = tok + 8 * slot;
        if (++slot == NSLOT) { slot = 0; par ^= 1; }
    }
    __device__ __forceinline__ void drain() { wg_wait<0>(); release(); }
    __device__ __forceinline__ void at(int stage) { slot = stage % NSLOT; par = (stage / NSLOT) & 1; }
};
enum { M_QKV, M_Q0KV, M_KV, M_GU3, M_GU2 };
template <int MODE, bool ZERO, bool OWN = false>
__device__ __forceinline__ void step32(float (&a256)[128], float (&a128)[64], Pipe& p, uint32_t wg, uint32_t own = 0) {
    constexpr uint32_t KS = MODE < M_KV ? 12288 : MODE == M_KV ? 8192 : 2048, LBO = MODE <= M_KV ? 2048 : 4096;
    constexpr uint32_t O256 = 8192 + (MODE < M_KV ? 4096 : 0), O128 = 8192 + (MODE < M_KV ? 0 : 16384);
    constexpr bool W128 = MODE == M_QKV || MODE == M_GU3;
    const uint32_t st = p.stage();
    wg_fence();
#pragma unroll
    for (int k = 0; k < 2; ++k) {
        const uint64_t da = OWN ? mk_desc(own, k * 32, 16, 1024, 1) : mk_desc(st + wg * 256, k * 32, 16, 512, 2);
        const uint64_t d0 = mk_desc(st, O256 + k * KS, LBO, 1024, 1), d1 = mk_desc(st, O128 + k * KS, LBO, 1024, 1);
        if (ZERO && k == 0) { wgmma_n256_z(a256, da, d0); if (W128) wgmma_n128_z(a128, da, d1); }
        else { wgmma_n256(a256, da, d0); if (W128) wgmma_n128(a128, da, d1); if (MODE == M_Q0KV) wgmma_n64<0>(a128, da, d1); }
    }
    p.issued();
}
struct Nop { __device__ __forceinline__ void operator()() const {} };
template <bool ZERO, class F = Nop>
__device__ __forceinline__ void step64(float (&acc)[64], Pipe& p, uint32_t wg, int own = -1, F landed = F()) {
    const uint32_t st = p.stage();
    landed();
    const uint32_t sa = own >= 0 ? d16(p.sb) + OFF_STG / 16 + wg * 512 + own * 1024 : st + wg * 512;
    wg_fence();
#pragma unroll
    for (int k = 0; k < 4; ++k) {
        const uint64_t da = mk_desc(sa, k * 32, 16, 1024, 1), db = mk_desc(st, 16384 + k * 2048, 8192, 1024, 1);
        if (ZERO && k == 0) wgmma_n128_z(acc, da, db); else wgmma_n128(acc, da, db);
    }
    p.issued();
}
__device__ __forceinline__ void run64_landed(float (&acc)[64], Pipe& p, uint32_t wg, int n) {
#pragma unroll 1
    while (true) {
        const uint32_t st = d16(p.sb) + p.slot * (SLOT >> 4);
        wg_fence();
#pragma unroll
        for (int k = 0; k < 4; ++k) wgmma_n128(acc, mk_desc(st + wg * 512, k * 32, 16, 1024, 1), mk_desc(st, 16384 + k * 2048, 8192, 1024, 1));
        p.issued();
        if (--n == 0) break;
        p.stage();
    }
}
__device__ __forceinline__ void rename(float (&d)[64], const float (&a)[64]) {
#pragma unroll
    for (int i = 0; i < 64; ++i) asm volatile("mov.b32 %0, %1;" : "=f"(d[i]) : "f"(a[i]));
}
template <int MODE, int ST>
__device__ __forceinline__ void run_own(float (&a256)[128], float (&a128)[64], Pipe& p, uint32_t wg) {
    const uint32_t a0 = d16(p.sb) + OFF_OWN / 16 + wg * 512;
    p.at(ST);
    step32<MODE, true, true>(a256, a128, p, wg, a0);
#pragma unroll 1
    for (int i = 1; i < 4; ++i) step32<MODE, false, true>(a256, a128, p, wg, a0 + (i >> 1) * 1024 + (i & 1) * 4);
    p.drain();
    mbar_arrive_if0(BAR_FULL(p.sb, 5), threadIdx.x & 127);
#pragma unroll 1
    for (int i = 0; i < 4; ++i) {
        if (i < 2) p.at(i ? ST + 6 : ST + 4);
        if (wg == 0) mbar_wait(BAR_ONE(p.sb, EV_A0 + i), ST > 0);
        step32<MODE, false>(a256, a128, p, wg);
    }
    p.at(ST + 9);
}
template <int LG, class Step>
__device__ __forceinline__ void run(int n, uint32_t wg, uint32_t ev, Step step) {
    const int last = LG ? (wg ? EARLY : LG) : 0;
#pragma unroll 1
    for (int part = 0; ; ++part) {
#pragma unroll 1
        for (int i = part ? last : n - last; i > 0; --i) step();
        if (part || !LG) break;
        mbar_arrive_if0(ev, threadIdx.x ^ 128);
        if (wg == 0) mbar_wait(ev, 0);
    }
}

struct LnRow { float rs0, nm0, rs1, nm1; };
__device__ __forceinline__ void publish_stats(uint4* dst, float s0, float q0, float s1, float q1, uint32_t tag) {
    st_pkt16(dst, (__float_as_uint(s0) & ~3u) | tag, __float_as_uint(s1), __float_as_uint(q0), __float_as_uint(q1));
}
template <class F = Nop>
__device__ __forceinline__ LnRow merge_stats(const uint4* src, uint32_t tag, F meanwhile = F()) {
    uint4 a = ld_pkt16(src), b = ld_pkt16(src + S_ / 2);
    meanwhile();
    while (!__all_sync(0xffffffffu, (a.x & b.x & tag) != 0)) { a = ld_pkt16(src); b = ld_pkt16(src + S_ / 2); }
    float v[4] = {__uint_as_float(a.x) + __uint_as_float(b.x), __uint_as_float(a.y) + __uint_as_float(b.y),
                  __uint_as_float(a.z) + __uint_as_float(b.z), __uint_as_float(a.w) + __uint_as_float(b.w)};
#pragma unroll
    for (int o = 1; o < 4; o <<= 1)
#pragma unroll
        for (int i = 0; i < 4; ++i) v[i] += __shfl_xor_sync(0xffffffffu, v[i], o);
    const float m0 = v[0] * (1.f / D_), m1 = v[1] * (1.f / D_);
    const float r0 = rsq(fmaxf(fmaf(-m0, m0, v[2] * (1.f / D_)), 0.f) + 1e-5f), r1 = rsq(fmaxf(fmaf(-m1, m1, v[3] * (1.f / D_)), 0.f) + 1e-5f);
    return LnRow{r0, -m0 * r0, r1, -m1 * r1};
}
__device__ __forceinline__ void ln_norm(uint32_t (&y)[32], const float (&x)[64], const LnRow& n) {
#pragma unroll
    for (int e = 0; e < 32; ++e) {
        const float rs = (e & 1) ? n.rs1 : n.rs0, nm = (e & 1) ? n.nm1 : n.nm0;
        y[e] = pack2(fmaf(x[2 * e], rs, nm), fmaf(x[2 * e + 1], rs, nm));
    }
}
__device__ __forceinline__ void ln_emit(const uint32_t (&y)[32], const uint4 (&p)[8], uint32_t sb, uint32_t wg, const Idx& ix) {
#pragma unroll
    for (int i = 0; i < 8; ++i) {
        uint32_t r[4];
#pragma unroll
        for (int e = 0; e < 4; ++e) r[e] = hfma2_bf16(y[4 * i + e], e < 2 ? p[i].z : p[i].w, e < 2 ? p[i].x : p[i].y);
        stsm4(sb + OFF_OWN + wg * 8192 + (i >> 2) * 16384 + (ix.pan ^ ((i & 3) << 5)), r[0], r[1], r[2], r[3]);
        if (i == 3) { __syncwarp(); if (ix.lane == 0) mbar_arrive(BAR_SFULL(sb, wg * 2)); }
    }
    fence_async_smem();
    __syncwarp();
    if (ix.lane == 0) mbar_arrive(BAR_SFULL(sb, wg * 2 + 1));
    bar_sync(1 + wg, 128);
}
template <int P>
__device__ __forceinline__ void load_panel(uint32_t (&r)[32], uint32_t p) {
    IDX();
#pragma unroll
    for (int i = 4 * P; i < 4 * P + 4; ++i) ldsm4(p + (pan_addr ^ ((i & 3) << 5)), r[4 * i], r[4 * i + 1], r[4 * i + 2], r[4 * i + 3]);
}
template <int E0 = 0, int E1 = 32>
__device__ __forceinline__ void widen(float (&x)[64], const uint32_t (&r)[32]) {
#pragma unroll
    for (int e = E0; e < E1; ++e) asm volatile("shl.b32 %0, %2, 16;\nand.b32 %1, %2, 0xFFFF0000;" : "=&f"(x[2 * e]), "=f"(x[2 * e + 1]) : "r"(r[e]));
}
template <int I0 = 0, int I1 = 8>
__device__ __forceinline__ void load_table(uint4 (&t)[8], uint32_t tab) {
#pragma unroll
    for (int i = I0; i < I1; ++i) t[i] = lds128(tab + i * 64 + (threadIdx.x & 3) * 16);
}
template <int STRIDE, int P0, int P1, class Step>
__device__ __forceinline__ void epilogue_operands(float (&x)[64], uint4 (&g)[8], uint32_t (&r)[32], uint32_t src, uint32_t tab, Step step) {
#pragma unroll
    for (int i = 0; i < 64; ++i) asm volatile("" : "=f"(x[i]));
#pragma unroll
    for (int i = 0; i < (P1 > 6 ? 8 : 0); ++i) asm volatile("" : "=r"(g[i].x), "=r"(g[i].y), "=r"(g[i].z), "=r"(g[i].w));
#pragma unroll 1
    for (int it = P0 * STRIDE; it < P1 * STRIDE; ++it) {
        step([&] {
            if (it == 0) load_panel<0>(r, src);
            if (it == STRIDE) load_panel<1>(r, src + 16384);
            if (it == 6 * STRIDE) load_table<0, 4>(g, tab);
            if (it == 7 * STRIDE) load_table<4, 8>(g, tab);
        });
        if (it == 2 * STRIDE) widen<0, 8>(x, r);
        if (it == 3 * STRIDE) widen<8, 16>(x, r);
        if (it == 4 * STRIDE) widen<16, 24>(x, r);
        if (it == 5 * STRIDE) widen<24, 32>(x, r);
    }
}
__device__ __forceinline__ float gate_of(const uint4 (&t)[8], int e) {
    const uint4 v = t[e >> 3];
    return __uint_as_float((e & 4) ? ((e & 1) ? v.w : v.z) : ((e & 1) ? v.y : v.x));
}
__device__ __forceinline__ constexpr int glu_at(int i, int e) { return (i >> 2) * 64 + ((i >> 1) & 1) * 16 + (e >> 1) * 4 + (i & 1) * 2 + (e & 1); }
struct Raw { const float (&a)[64]; __device__ __forceinline__ float operator()(int e) const { return a[e]; } };
struct Packed {
    const uint32_t (&a)[64];
    __device__ __forceinline__ float operator()(int e) const {
        float v;
        if (e & 1) asm volatile("and.b32 %0, %1, 0xFFFF0000;" : "=f"(v) : "r"(a[e >> 1])); else asm volatile("shl.b32 %0, %1, 16;" : "=f"(v) : "r"(a[e >> 1]));
        return v;
    }
};
template <class A>
__device__ __forceinline__ void glu_tanh(float (&t)[8], A a, int i) {
#pragma unroll
    for (int e = 0; e < 8; ++e) asm volatile("tanh.approx.f32 %0, %1;" : "=f"(t[e]) : "f"(a(glu_at(i, e))));
}
template <bool FENCE, class A>
__device__ __forceinline__ void glu_store(const float (&t)[8], A a, int i, __nv_bfloat16* dst) {
    uint32_t r[4];
#pragma unroll
    for (int c = 0; c < 4; ++c) {
        const float u0 = a(32 + glu_at(i, 2 * c)), u1 = a(33 + glu_at(i, 2 * c));
        r[c] = pack2(fmaf(t[2 * c], u0, u0), fmaf(t[2 * c + 1], u1, u1));
    }
    if (!FENCE) asm volatile("st.global.v4.u32 [%0], {%1, %2, %3, %4};" :: "l"(dst + (i & 1) * 8 * F_ + (i >> 1) * 32), "r"(r[0]), "r"(r[1]), "r"(r[2]), "r"(r[3]) : "memory");
    else asm volatile("{\n.reg .pred p;\nsetp.eq.u32 p, %5, %6;\nG_LOOP:\nst.global.v4.u32 [%0], {%1, %2, %3, %4};\n@p bra G_LOOP;\n}"
        :: "l"(dst + (i & 1) * 8 * F_ + (i >> 1) * 32), "r"(r[0]), "r"(r[1]), "r"(r[2]), "r"(r[3]), "r"(blockIdx.y), "r"(1000 + i) : "memory");
}
__device__ __forceinline__ void glu_now(const float (&a)[64], __nv_bfloat16* dst) {
    float t[2][8];
#pragma unroll
    for (int i = 0; i <= 4; ++i) {
        if (i < 4) glu_tanh(t[i & 1], Raw{a}, i);
        if (i > 0) glu_store<true>(t[(i - 1) & 1], Raw{a}, i - 1, dst);
    }
}
template <class Step>
__device__ __forceinline__ void glu_under(uint32_t (&a)[64], __nv_bfloat16* dst, int n, Step step) {
#pragma unroll 1
    for (int it = -n; it < 16; ++it) {
        step();
        if (it >= 0 && !(it & 1)) {
#pragma unroll
            for (int i = 0; i < 4; ++i)
                if ((it & 7) == 2 * i) {
                    float t[8];
                    glu_tanh(t, Packed{a}, i); glu_store<false>(t, Packed{a}, i, dst);
#pragma unroll
                    for (int c = 0; c < 8; ++c) { const int e = (glu_at(i, (2 * c) & 7) >> 1) + (c >> 2) * 16; a[e] = a[32 + e]; }
                    if (i == 3) dst += 64;
                }
        }
    }
}
__device__ __forceinline__ void pack_all(uint32_t (&d)[64], const float (&a)[128]) {
#pragma unroll
    for (int i = 0; i < 64; ++i) d[i] = pack2(a[2 * i], a[2 * i + 1]);
}

__global__ void __launch_bounds__(384, 1)
fused_block_kernel(const __grid_constant__ Ptrs pt, const __grid_constant__ Maps mp) {
    uint32_t* const g_flags = pt.mail->flags;
    uint2* const g_mod = pt.mail->mod;
    uint4* const g_st1 = pt.mail->st1;
    uint32_t* const g_par2 = pt.mail->par2;
    uint4* const g_halo = pt.mail->halo;
    const __nv_bfloat16* __restrict__ cvec = pt.c;
    asm volatile("{\n.reg .pred p;\nsetp.eq.u32 p, %1, 1;\n@p prefetch.global.L2 [%0];\n}"
        :: "l"(pt.x + ((blockIdx.x & 127) * 16 + ((threadIdx.x >> 4) & 7) * 2 + 1) * D_ + (threadIdx.x & 15) * 64), "r"(threadIdx.x >> 7));
    if (threadIdx.x == 0) { prefetch_map(&mp.x); prefetch_map(&mp.wm); }
    uint32_t ep = 0;
#define LOAD_EP() asm volatile("ld.relaxed.gpu.global.u32 %0, [%1];" : "=r"(ep) : "l"(&g_flags[FL_DONE + (threadIdx.x & blockIdx.y)]) : "memory")
    if (threadIdx.x >= 256) LOAD_EP();
    extern __shared__ __align__(1024) uint8_t smem[];
    const uint32_t sb = smem_u32(smem) + 1024;
    const uint32_t tid = threadIdx.x, tw = tid & 127, lane = tid & 31;
    const uint32_t warp = __shfl_sync(0xffffffffu, tid >> 5, 0), wg = warp >> 2;
    uint32_t rank; asm("mov.u32 %0, %%cluster_ctarank;" : "=r"(rank));
    rank = __shfl_sync(0xffffffffu, rank, 0);
    uint32_t smid; asm volatile("mov.u32 %0, %%smid;" : "=r"(smid));
    const int c = __shfl_sync(0xffffffffu, smid >> 1, 0);
    const int q7 = ((c - 32) * 37) >> 8;
    const bool aux = (c >> 1) == 30;
    const int grp = c < 32 ? c & 7 : c < 60 ? c - 31 - 7 * q7 : 0;
    const int jhi = aux ? (c - 60) * 2 + rank : c - 58, jlo = c < 32 ? c >> 3 : 4 + q7, j = c < 60 ? jlo : jhi;
    const int m = grp * 2 + rank;
    const int cid = (c < 60 ? c : c - 2) * 2 + rank;
    if (warp == 1 && !aux && elect_one()) {
        mbar_init(BAR_ONE(sb, EV_X1), 1);
        mbar_expect_tx(BAR_ONE(sb, EV_X1), 16384);
#pragma unroll
        for (int i = 0; i < 2; ++i) tma_load(sb + OFF_STG + i * 16384 + 8192, &mp.x, D_ + j * 128 + i * 64, m * 64, BAR_ONE(sb, EV_X1));
#pragma unroll
        for (int i = 0; i < 4; ++i) mbar_init(BAR_ONE(sb, EV_WIN + i), 1);
#pragma unroll
        for (int i = 0; i < 4; ++i) {
            mbar_expect_tx(BAR_ONE(sb, EV_WIN + i), 8192);
            tma_load(sb + OFF_OWN + i * 8192, &mp.wm, (cid >> 2) * 64, (cid & 3) * 256 + i * 64, BAR_ONE(sb, EV_WIN + i));
        }
        asm volatile("fence.mbarrier_init.release.cluster;" ::: "memory");
    }
    __syncwarp();

    bool cluster_arrive_early = false;
    if (wg < 2) {
      cluster_arrive();
      if (aux) {
        LOAD_EP();
        cluster_wait();
        ep = __shfl_sync(0xffffffffu, ep, 0) / NCTA + 1;
        Ring r{0, 0};
#pragma unroll 1
        for (int p = 0; p < 4; ++p) {
            float acc[64];
#pragma unroll
            for (int i = 0; i < 64; ++i) acc[i] = 0.f;
#pragma unroll 1
            for (int kc = 0; kc < 16; ++kc) {
                mbar_wait(BAR_FULL(sb, r.slot), r.par);
                wg_fence();
#pragma unroll
                for (int k = 0; k < 4; ++k)
                    wgmma_n128(acc, mk_desc(d16(sb) + kc * 64, OFF_STG + k * 32, 16, 0, 1), mk_desc(d16(sb) + r.slot * (SLOT >> 4) + wg * 1024, k * 2048, 8192, 1024, 1));
                wg_commit();
                wg_wait<0>();
                mbar_arrive_if0(BAR_EMPTY(sb, r.slot), tw);
                r.next();
            }
            if (tw < 32) {
                if (tw < 4) {
#pragma unroll
                    for (int jn = 0; jn < 16; ++jn) sts32(sb + OFF_TAB + wg * 256 + (jn * 4 + tw) * 4, pack2(acc[jn * 4], acc[jn * 4 + 1]));
                }
                __syncwarp();
#pragma unroll 1
                for (uint32_t t = wg * 64 + tw; t < wg * 64 + 64; t += 32) {
                    const uint32_t val = lds32(sb + OFF_TAB + t * 4);
                    const float one = p == 2 ? 1.f : 0.f;
                    if (p == 0 || p == 3) st_pkt(g_mod + (8 + p * 4 + j) * 128 + t, val, ep);
                    else g_par2[(j * 16 + (t >> 3)) * 16 + (t & 3) * 4 + (p - 1) * 2 + ((t >> 2) & 1)] = pack2(0.5f * bf_round(one + bf_lo(val)), 0.5f * bf_round(one + bf_hi(val)));
                }
                __syncwarp();
                if (tw == 0 && p == 2) asm volatile("red.release.gpu.global.add.u32 [%0], 1;" :: "l"(&g_flags[FL_LN2]) : "memory");
            }
        }
      } else {
        Pipe pp{sb, 0, 0, 0, 0};
        pp.arm();
        {
            IDX();
            uint4* const st1 = g_st1 + m * 64 + warp * 8 + g8;
            if (q4 == (g8 >> 1)) st_pkt16(st1 + j * (S_ / 2), 0, 0, 0, 0);
            cluster_wait();
            uint32_t xr[32];
            mbar_wait(BAR_ONE(sb, wg ? EV_X1 : EV_X), 0);
            float sm[4] = {0.f, 0.f, 0.f, 0.f}, g0[4] = {0.f, 0.f, 0.f, 0.f}, g1[4] = {0.f, 0.f, 0.f, 0.f};
#pragma unroll
            for (int i = 0; i < 8; ++i) {
                ldsm4(sb + OFF_STG + wg * 8192 + (i >> 2) * 16384 + (pan_addr ^ ((i & 3) << 5)), xr[4 * i], xr[4 * i + 1], xr[4 * i + 2], xr[4 * i + 3]);
                mma16816(sm, xr[4 * i], xr[4 * i + 1], xr[4 * i + 2], xr[4 * i + 3], 0x3F803F80u, 0x3F803F80u);
                mma16816(g0, xr[4 * i], xr[4 * i + 1], xr[4 * i + 2], xr[4 * i + 3], xr[4 * i], xr[4 * i + 2]);
                mma16816(g1, xr[4 * i], xr[4 * i + 1], xr[4 * i + 2], xr[4 * i + 3], xr[4 * i + 1], xr[4 * i + 3]);
            }
            if (q4 == (g8 >> 1))
                publish_stats(st1 + j * (S_ / 2), sm[0], (g8 & 1) ? g0[1] : g0[0], sm[2], (g8 & 1) ? g1[3] : g1[2], 1);
            float xf[64];
            widen(xf, xr);
            mbar_wait(BAR_ONE(sb, EV_WINL), 0);
            const LnRow n1 = merge_stats(st1 + q4 * S_, 1);
            mbar_arrive_if0(BAR_ONE(sb, EV_ST0), tid & 159);
            ln_norm(xr, xf, n1);
            asm volatile("setmaxnreg.inc.sync.aligned.u32 %0;" :: "n"(RC));
            mbar_wait(BAR_ONE(sb, EV_PAR), 0);
            uint4 par[8];
            load_table(par, sb + OFF_PAR);
            ln_emit(xr, par, sb, wg, ix);
        }
        uint32_t xr[32];
        {
            float qa[64];
            uint32_t kl[16], kh[16], kp[16];
            uint32_t v0[32], v1[32];
            {
                float kv[128];
                float q1[64], q2[64];
                run_own<M_QKV, 0>(kv, q1, pp, wg);
                run<0>(24 - 2 * NS - 2 * NQ, wg, 0, [&] { step32<M_QKV, false>(kv, q1, pp, wg); });
                pp.drain();
                rename(q2, q1);
                run<0>(2 * NS, wg, 0, [&] { step32<M_Q0KV, false>(kv, q2, pp, wg); });
                pp.drain();
                rename(qa, q2);
                run<LAGQ>(2 * NQ, wg, BAR_ONE(sb, EV_LAG0), [&] { step32<M_KV, false>(kv, qa, pp, wg); });
                pp.stage();
                pp.drain();
                IDX();
#pragma unroll
                for (int t = 0; t < 16; ++t) v1[(t >> 1) * 4 + 2 + (t & 1)] = movm(pack2(kv[66 + 4 * t], kv[67 + 4 * t]));
#pragma unroll
                for (int t = 0; t < 16; ++t) {
                    kl[t] = pack2(kv[4 * t], kv[4 * t + 1]); kh[t] = pack2(kv[4 * t + 2], kv[4 * t + 3]);
                    v1[(t >> 1) * 4 + (t & 1)] = pack2(kv[64 + 4 * t], kv[65 + 4 * t]);
                }
                if (w4 < 3) {
                    const uint32_t dst = sb + OFF_STG + wg * 8192 + (w4 >> 1) * 16384 + (w4 & 1) * 4096;
#pragma unroll
                    for (int i = 0; i < 4; ++i) sts128(dst + i * 512 + lane * 16, kh[4 * i], kh[4 * i + 1], kh[4 * i + 2], kh[4 * i + 3]);
#pragma unroll
                    for (int i = 0; i < 8; ++i) sts64(dst + 2048 + i * 256 + lane * 8, v1[4 * i + 2], v1[4 * i + 3]);
                } else if (m < 15) {
                    uint4* const dst = g_halo + (m * 8 + j) * 512 + wg * 256;
#pragma unroll
                    for (int i = 0; i < 4; ++i) { if (!kh[4 * i]) kh[4 * i] = 0x8000u; st_pkt16(dst + i * 32 + lane, kh[4 * i], kh[4 * i + 1], kh[4 * i + 2], kh[4 * i + 3]); }
#pragma unroll
                    for (int i = 0; i < 8; ++i) { if (!v1[4 * i + 2]) v1[4 * i + 2] = 0x8000u; st_pkt((uint2*)(dst + 128) + i * 32 + lane, v1[4 * i + 2], v1[4 * i + 3]); }
                }
            }
            pp.at(ST_Q);
            run64_landed(qa, pp, wg, QA);
            pp.stage();
            IDX();
            uint4* const halo = g_halo + ((m - 1) * 8 + j) * 512 + wg * 256;
            auto fetch_halo = [&] {
#pragma unroll
                for (int i = 0; i < 4; ++i) {
                    const uint4 t = m > 0 ? ld_pkt16(halo + i * 32 + lane) : make_uint4(0, 0, 0, 0);
                    kp[4 * i] = t.x; kp[4 * i + 1] = t.y; kp[4 * i + 2] = t.z; kp[4 * i + 3] = t.w;
                }
#pragma unroll
                for (int i = 0; i < 8; ++i) {
                    const uint2 t = m > 0 ? ld_pkt((const uint2*)(halo + 128) + i * 32 + lane) : make_uint2(0, 0);
                    v0[4 * i] = t.x; v0[4 * i + 1] = t.y;
                }
            };
            bar_sync(1 + wg, 128);
#pragma unroll
            for (int t = 0; t < 16; ++t) v1[(t >> 1) * 4 + (t & 1)] = movm(v1[(t >> 1) * 4 + (t & 1)]);
            if (w4 == 0) fetch_halo();
            else {
                const uint32_t src = sb + OFF_STG + wg * 8192 + ((w4 - 1) >> 1) * 16384 + ((w4 - 1) & 1) * 4096;
#pragma unroll
                for (int i = 0; i < 4; ++i) { const uint4 t = lds128(src + i * 512 + lane * 16); kp[4 * i] = t.x; kp[4 * i + 1] = t.y; kp[4 * i + 2] = t.z; kp[4 * i + 3] = t.w; }
#pragma unroll
                for (int i = 0; i < 8; ++i) { const uint2 t = lds64(src + 2048 + i * 256 + lane * 8); v0[4 * i] = t.x; v0[4 * i + 1] = t.y; }
            }
            pp.at(ST_Q + QA);
            run64_landed(qa, pp, wg, NQ - QA);
#pragma unroll
            for (int t = 0; t < 16; ++t) asm volatile("mov.b32 %0, %1;" : "=r"(v0[(t >> 1) * 4 + 2 + (t & 1)]) : "r"(v1[(t >> 1) * 4 + (t & 1)]));
            bar_sync(1 + wg, 128);
            if (w4 == 0 && m > 0) {
                while (true) {
                    bool ok = true;
#pragma unroll
                    for (int i = 0; i < 8; ++i) ok = ok && v0[4 * i] != 0 && kp[4 * (i & 3)] != 0;
                    if (__all_sync(0xffffffffu, ok)) break;
                    fetch_halo();
                }
            }
            pp.drain();
            float qb[64];
            rename(qb, qa);
            const bool lo0 = q4 * 2 > g8, lo1 = q4 * 2 + 1 > g8;
            const bool nopast = m == 0 && w4 == 0;
            const uint32_t lomask = (lo0 ? 0xFFFFu : 0u) | (lo1 ? 0xFFFF0000u : 0u);
            const float sl2 = 0.17677669529663687f * 1.4426950408889634f;
            const uint32_t oa = wg * 8192 + (w4 * 16 + (lane & 7)) * 128 + (((lane >> 3) ^ (lane & 7)) << 4);
#pragma unroll
            for (int hp = 0; hp < 2; ++hp) {
                if (hp) {
                    bar_sync(3, 256);
#pragma unroll 1
                    for (int it = 0; it < NS; ++it) {
                        pp.slot = (SWEEP >> (4 * it)) & 7; pp.par = (SWEEP >> (4 * it + 3)) & 1;
                        const uint32_t st = pp.stage();
                        wg_fence();
#pragma unroll
                        for (int k = 0; k < 4; ++k) wgmma_n64<32>(qb, mk_desc(st + wg * 512, k * 32, 16, 1024, 1), mk_desc(st, 16384 + k * 2048, 8192, 1024, 1));
                        pp.issued();
                        if (it == 0) pp.rel = 0;
                        if (it == SWO && pp.tok) asm volatile("mbarrier.arrive.shared::cluster.b64 _, [%0];" :: "r"(pp.tok + 8 * (SWEEP & 7)) : "memory");
                    }
                    mbar_wait(BAR_FULL(sb, ST_WO % NSLOT), (ST_WO / NSLOT) & 1);
                    pp.drain();
                    load_panel<0>(xr, sb + ST_WO % NSLOT * SLOT + wg * 8192);
                }
                float e0[4], e1[4], mx[4], sum[4];
#pragma unroll
                for (int hh = 0; hh < 2; ++hh) {
                    const int h = 2 * hp + hh;
                    uint32_t qf[8];
                    float s[3][4];
#pragma unroll
                    for (int i = 0; i < 8; ++i) qf[i] = pack2(qb[16 * h + 2 * i], qb[16 * h + 2 * i + 1]);
#pragma unroll
                    for (int nt = 0; nt < 3; ++nt) {
                        const uint32_t (&kk)[16] = nt == 0 ? kp : nt == 1 ? kl : kh;
                        s[nt][0] = s[nt][1] = s[nt][2] = s[nt][3] = 0.f;
                        mma16816(s[nt], qf[0], qf[1], qf[2], qf[3], kk[4 * h], kk[4 * h + 1]);
                        mma16816(s[nt], qf[4], qf[5], qf[6], qf[7], kk[4 * h + 2], kk[4 * h + 3]);
                    }
#pragma unroll
                    for (int hf = 0; hf < 2; ++hf) {
                        e0[2 * hh + hf] = lo0 ? ((hf == 0 && nopast) ? -INFINITY : s[hf][hf * 2]) : s[hf + 1][hf * 2];
                        e1[2 * hh + hf] = lo1 ? ((hf == 0 && nopast) ? -INFINITY : s[hf][hf * 2 + 1]) : s[hf + 1][hf * 2 + 1];
                        mx[2 * hh + hf] = fmaxf(e0[2 * hh + hf], e1[2 * hh + hf]);
                    }
                }
#pragma unroll
                for (int o = 1; o < 4; o <<= 1)
#pragma unroll
                    for (int u = 0; u < 4; ++u) mx[u] = fmaxf(mx[u], __shfl_xor_sync(0xffffffffu, mx[u], o));
#pragma unroll
                for (int u = 0; u < 4; ++u) {
                    const float c = -mx[u] * sl2;
                    e0[u] = ex2(fmaf(e0[u], sl2, c)); e1[u] = ex2(fmaf(e1[u], sl2, c));
                    sum[u] = e0[u] + e1[u];
                }
#pragma unroll
                for (int o = 1; o < 4; o <<= 1)
#pragma unroll
                    for (int u = 0; u < 4; ++u) sum[u] += __shfl_xor_sync(0xffffffffu, sum[u], o);
#pragma unroll
                for (int u = 0; u < 4; ++u) {
                    const int h = 2 * hp + (u >> 1), hf = u & 1;
                    const uint32_t (&vv)[32] = hf ? v1 : v0;
                    const float iv = rcp(sum[u]);
                    const uint32_t pr = pack2(e0[u] * iv, e1[u] * iv);
                    float o[2][4];
#pragma unroll
                    for (int t = 0; t < 2; ++t) {
                        o[t][0] = o[t][1] = o[t][2] = o[t][3] = 0.f;
                        mma16816(o[t], vv[8 * h + 4 * t], vv[8 * h + 4 * t + 1], vv[8 * h + 4 * t + 2], vv[8 * h + 4 * t + 3], pr & lomask, pr & ~lomask);
                    }
                    stsm4t(sb + OFF_STG + hp * 16384 + (oa ^ ((h & 1) << 6)) + hf * 1024, pack2(o[0][0], o[0][1]), pack2(o[0][2], o[0][3]), pack2(o[1][0], o[1][1]), pack2(o[1][2], o[1][3]));
                }
                __syncwarp();
                if (lane == 0) mbar_arrive(BAR_SFULL(sb, wg * 2 + hp));
            }
        }
        {
            float acc[64], xf[64];
            uint4 gt[8], par[8];
            fence_async_smem();
            bar_sync(3, 256);
            pp.at(ST_WO);
            mbar_wait(BAR_FULL(sb, (ST_WO + 1) % NSLOT), ((ST_WO + 1) / NSLOT) & 1);
            step64<true>(acc, pp, wg, 0, [&] { load_panel<1>(xr, sb + (ST_WO + 1) % NSLOT * SLOT + wg * 8192); });
            step64<false>(acc, pp, wg, 1);
            fence_async_smem();
            bar_sync(1 + wg, 128);
            mbar_wait(BAR_ONE(sb, EV_GA), 0);
            load_table(gt, sb + OFF_TAB);
            pp.drain();
            uint4* const pub = g_st1 + __shfl_sync(0xffffffffu, j * (S_ / 2) + m * 64 + (tid >> 2), lane);
            pp.at(ST_WO + 2);
            epilogue_operands<1, 2, 6>(xf, gt, xr, 0, sb + OFF_TAB, [&](auto f) { step64<false>(acc, pp, wg, -1, f); });
            run<LAGW>(10, wg, BAR_ONE(sb, EV_LAG4), [&] { step64<false>(acc, pp, wg); });
            pp.drain();
            float su[4] = {0.f, 0.f, 0.f, 0.f}, sq[4] = {0.f, 0.f, 0.f, 0.f};
#pragma unroll
            for (int e = 0; e < 64; ++e) {
                xf[e] = fmaf(gate_of(gt, e), acc[e], xf[e]);
                su[e & 3] += xf[e]; sq[e & 3] = fmaf(xf[e], xf[e], sq[e & 3]);
            }
            {
                float v[4] = {su[0] + su[1], sq[0] + sq[1], su[2] + su[3], sq[2] + sq[3]};
#pragma unroll
                for (int o = 1; o < 4; o <<= 1)
#pragma unroll
                    for (int i = 0; i < 4; ++i) v[i] += __shfl_xor_sync(0xffffffffu, v[i], o);
                if ((tid & 3) == 0) publish_stats(pub, v[0], v[1], v[2], v[3], 2);
            }
            IDX();
            mbar_wait(BAR_ONE(sb, EV_P2), 0);
#pragma unroll
            for (int i = 0; i < 8; ++i)
                stsm4(sb + OFF_STG + wg * 8192 + (i >> 2) * 16384 + (pan_addr ^ ((i & 3) << 5)), pack2(xf[8 * i], xf[8 * i + 1]), pack2(xf[8 * i + 2], xf[8 * i + 3]),
                      pack2(xf[8 * i + 4], xf[8 * i + 5]), pack2(xf[8 * i + 6], xf[8 * i + 7]));
            load_table(par, sb + OFF_PAR);
            const LnRow n2 = merge_stats(pub + ((int)q4 * 2 - j) * (S_ / 2), 2, [&] {
                mbar_wait(BAR_EMPTY(sb, (ST_GU - 1) % NSLOT), ((ST_GU - 1) / NSLOT) & 1);
            });
            ln_norm(xr, xf, n2);
            ln_emit(xr, par, sb, wg, ix);
        }
        {
            auto h_at = [&](int col) { IDX(); return pt.hb + (m * 128 + warp * 16 + g8) * F_ + j * 448 + col + q4 * 8; };
            uint32_t gu[64];
            {
                float a256[128], a128[64];
                run_own<M_GU3, ST_GU>(a256, a128, pp, wg);
                run<LAG>(24, wg, BAR_ONE(sb, EV_LAG1), [&] { step32<M_GU3, false>(a256, a128, pp, wg); });
                __nv_bfloat16* const dst = h_at(128);
                pp.drain();
                glu_now(a128, dst);
                pack_all(gu, a256);
            }
#pragma unroll 1
            for (int p = 0; p < 2; ++p) {
                float b256[128], none[64];
                pp.at(p ? ST_G1 + 32 : ST_G1);
                step32<M_GU2, true>(b256, none, pp, wg);
                glu_under(gu, h_at(p * 192), GW + wg, [&] { step32<M_GU2, false>(b256, none, pp, wg); });
                __syncwarp();
                mbar_arrive_if0(BAR_ONE(sb, EV_HB), lane);
                run<LAGS>(15 - GW - wg, wg, BAR_ONE(sb, EV_LAG2 + p), [&] { step32<M_GU2, false>(b256, none, pp, wg); });
                pp.drain();
                pack_all(gu, b256);
            }
            float acc[64], xf[64];
            uint4 gt[8];
            pp.at(ST_G1 + 64);
            step64<true>(acc, pp, wg);
            glu_under(gu, h_at(320), GD + wg, [&] { step64<false>(acc, pp, wg); });
            __syncwarp();
            mbar_arrive_if0(BAR_ONE(sb, EV_HB), lane);
            uint32_t x1[32];
#pragma unroll
            for (int i = 0; i < 32; ++i) asm volatile("" : "=r"(x1[i]));
            mbar_wait(BAR_ONE(sb, EV_GB), 0);
            epilogue_operands<2, 0, 8>(xf, gt, x1, sb + OFF_STG + wg * 8192, sb + OFF_TAB + 512, [&](auto f) { step64<false>(acc, pp, wg, -1, f); });
            const uint32_t rows = sb + OFF_STG + wg * 8192 + (warp & 3) * 2048;
            const uint32_t oa = __shfl_sync(0xffffffffu, rows + (lane & 7) * 128 + (((lane >> 3) ^ (lane & 7)) << 4), lane);
            run<LAGD>(23 - GD - wg, wg, BAR_ONE(sb, EV_LAG5), [&] { step64<false>(acc, pp, wg); });
            cluster_arrive();
            mbar_arrive_if0(BAR_SFULL(sb, wg * 2), lane);
            wg_wait<0>();
#pragma unroll
            for (int u = 0; u < 4; ++u) {
                const int p = u >> 1, hf = u & 1;
#pragma unroll
                for (int i = 0; i < 2; ++i) {
                    uint32_t r[4];
#pragma unroll
                    for (int t = 0; t < 4; ++t) {
                        const int e = 32 * p + 16 * i + 4 * t + 2 * hf;
                        r[t] = pack2(fmaf(gate_of(gt, e), acc[e], xf[e]), fmaf(gate_of(gt, e + 1), acc[e + 1], xf[e + 1]));
                    }
                    stsm4((oa ^ (i << 6)) + p * 16384 + hf * 1024, r[0], r[1], r[2], r[3]);
                }
                {
                    if (u < 3) asm volatile("{\n.reg .pred p;\nsetp.eq.u32 p, %0, %1;\nO_LOOP:\nfence.proxy.async.shared::cta;\n@p bra O_LOOP;\n}" :: "r"(blockIdx.y), "r"(2000 + u) : "memory");
                    else fence_async_smem();
                    __syncwarp();
                    if (elect_one()) tma_store(&mp.out, wg * D_ + j * 128 + p * 64, m * 64 + (warp & 3) * 16 + hf * 8, rows + p * 16384 + hf * 1024);
                }
            }
            bulk_commit();
        }
      }
    } else {
        const bool sil = aux || warp == 9 || warp == 10;
        uint4 cv;
        if (sil) cv = *(const uint4*)(cvec + ((aux ? warp : cid) & 3) * 256 + lane * 8);
        uint4* const modp = pt.mail->mod1 + (lane >> 2) * 2048 + (cid & 3) * 512 + ((cid >> 2) * 4 + (warp & 3)) * 4 + (lane & 3);
        if (!aux) st_pkt16(modp, 0, 0, 0, 0);
        uint4 sg = make_uint4(0, 0, 0, 0);
        if (lane < NSEG) sg = pt.sched[(aux ? 2 : warp == 11) * NSEG + lane];
        if (elect_one()) {
            if (warp == 8) {
                prefetch_map(&mp.ld[aux ? L_WMOD : L_WQKV]);
            } else if (warp < 11) {
#pragma unroll
                for (int i = 0; i < 3; ++i) mbar_init(BAR_FULL(sb, (warp - 9) * 3 + i), aux ? 1 : 2);
#pragma unroll
                for (int i = 0; i < 2; ++i) mbar_init(BAR_SFULL(sb, (warp - 9) * 2 + i), 4);
#pragma unroll
                for (int i = 0; i < 3; ++i) mbar_init(BAR_EMPTY(sb, (warp - 9) * 3 + i), aux ? 2 : 4);
            } else {
#pragma unroll
                for (int i = EV_X; i < EV_COUNT; ++i) mbar_init(BAR_ONE(sb, i), i == EV_HB ? 8 : i == EV_ST0 ? 4 : i == EV_P2 ? 2 : 1);
            }
            asm volatile("fence.mbarrier_init.release.cluster;" ::: "memory");
        }
        __syncwarp();
        cluster_arrive();
        cluster_wait();
        const bool el = elect_one();
        const int kown = j * 128;
        auto first_tiles = [&](int i0, int i1) {
#pragma unroll 1
            for (int i = i0; i < i1; ++i) {
                if (el && i < 4) mbar_arrive(BAR_FULL(sb, i));
                if (el) {
                    mbar_expect_tx(BAR_FULL(sb, i), 24576);
                    tma_load5_mc(sb + i * SLOT + 8192 + rank * 12288, &mp.ld[L_WQKV], 0, (i < 4 ? kown + i * 32 : j ? 0 : 128) + rank * 16, 2 * j, 0, 0, BAR_FULL(sb, i));
                }
            }
        };
        if (!aux && warp == 8) {
            mbar_wait(BAR_ONE(sb, EV_WIN), 0);
            if (el) {
                mbar_expect_tx(BAR_ONE(sb, EV_X), 16384);
#pragma unroll
                for (int i = 0; i < 2; ++i) tma_load(sb + OFF_STG + i * 16384, &mp.x, j * 128 + i * 64, m * 64, BAR_ONE(sb, EV_X));
            }
            first_tiles(0, NB0);
        }
        if (sil) {
            const uint32_t s0 = pack2(silu_(bf_lo(cv.x)), silu_(bf_hi(cv.x))), s1 = pack2(silu_(bf_lo(cv.y)), silu_(bf_hi(cv.y))),
                           s2 = pack2(silu_(bf_lo(cv.z)), silu_(bf_hi(cv.z))), s3 = pack2(silu_(bf_lo(cv.w)), silu_(bf_hi(cv.w)));
#pragma unroll
            for (int i = 0; i < 4; ++i) {
                const uint32_t row = aux ? 0 : (warp & 1) * 4 + i;
                sts128(sb + (aux ? OFF_STG + (warp & 3) * 4096 : 4 * SLOT) + (lane >> 3) * 1024 + row * 128 + (((lane & 7) ^ row) << 4), s0, s1, s2, s3);
            }
            fence_async_smem();
        }
        bar_sync(4, 128);
        if (!aux) {
            float acc[32];
#pragma unroll
            for (int i = 0; i < 32; ++i) acc[i] = 0.f;
#pragma unroll 1
            for (int h = 0; h < 4; ++h) {
                mbar_wait(BAR_ONE(sb, EV_WIN + h), 0);
                wg_fence();
#pragma unroll
                for (int k = 0; k < 4; ++k)
                    wgmma_n64<0>(acc, mk_desc(d16(sb) + h * 64, 4 * SLOT + (k >> 2) * 1024 + (k & 3) * 32, 16, 0, 1), mk_desc(d16(sb) + h * 512, OFF_OWN + k * 2048, 8192, 1024, 1));
                wg_commit();
            }
            ep = __shfl_sync(0xffffffffu, ep, 0) / NCTA + 1;
            wg_wait<0>();
            const uint32_t i = warp & 3;
            auto pick = [&](int e) { return __float_as_uint(i & 2 ? (i & 1 ? acc[24 + e] : acc[16 + e]) : (i & 1 ? acc[8 + e] : acc[e])); };
            st_pkt16(modp, (pick(0) & ~3u) | (1 + (ep & 1)), pick(1), pick(4), pick(5));
        } else if (warp == 8) {
            ep = __shfl_sync(0xffffffffu, ep, 0) / NCTA + 1;
            while (!(ld_pkt16(pt.mail->mod1 + 256).x & (1 + (ep & 1)))) __nanosleep(200);
        }
        asm volatile("setmaxnreg.dec.sync.aligned.u32 %0;" :: "n"(504 - 2 * RC));

        if (warp == 8 || (warp == 11 && !aux)) {
            const bool act = warp == 11;
            if (act) {
                const uint4* pk = pt.mail->mod1 + grp * 2048 + j * 32 + lane;
                uint4 a[8];
                while (true) {
                    uint32_t t = 1 + (ep & 1);
#pragma unroll
                    for (int i = 0; i < 8; ++i) { a[i] = ld_pkt16(pk + i * 256); t &= a[i].x; a[i].x &= ~3u; }
                    if (__all_sync(0xffffffffu, t != 0)) break;
                }
                uint32_t r[4];
#pragma unroll
                for (int v = 0; v < 2; ++v) {
                    auto sum = [&](uint32_t uint4::*f) { return bf_round((__uint_as_float(a[v].*f) + __uint_as_float(a[2 + v].*f)) + (__uint_as_float(a[4 + v].*f) + __uint_as_float(a[6 + v].*f))) + v; };
                    r[2 * v] = pack2(sum(&uint4::x), sum(&uint4::y)); r[2 * v + 1] = pack2(sum(&uint4::z), sum(&uint4::w));
                }
                sts128(sb + OFF_PAR + lane * 16, r[0], r[1], r[2], r[3]);
                __syncwarp();
                if (el) mbar_arrive(BAR_ONE(sb, EV_PAR));
            }
            {
                const uint32_t split = sg.z >> 20, bytes = (sg.z & 63) << 10;
                const uint32_t dst = split ? (split >= 3 ? 16384 : 8192) + rank * (split == 2 ? 4096 : bytes >> 1) : 0;
                const uint32_t blk = ((sg.z >> 8) & 15) * j + ((sg.z >> 12) & 255) + (split == 3 ? rank : 0);
                if (split == 2) sg.x += rank << 24;
                if (split == 1 || split == 4) sg.y |= rank << (12 + (split >> 2));
                sg.z = dst | blk << 16 | (sg.z & 63) << 24;
            }
            if (!act && !aux) {
#pragma unroll 1
                for (int h = 0; h < 2; ++h) { mbar_wait(BAR_ONE(sb, h ? EV_ST0 : EV_PAR), 0); first_tiles(h ? NB1 : NB0, h ? 5 : NB1); }
            }
            Ring r{0, 1};
#pragma unroll 1
            for (int s = 0; ; ++s) {
                const uint32_t x = __shfl_sync(0xffffffffu, sg.x, s), y = __shfl_sync(0xffffffffu, sg.y, s), z = __shfl_sync(0xffffffffu, sg.z, s), w = __shfl_sync(0xffffffffu, sg.w, s);
                const uint32_t nx = __shfl_sync(0xffffffffu, sg.x, s + 1);
                if (!x) break;
                if (el) { prefetch_map(&mp.ld[nx >> 24]); prefetch_map(&mp.ld[(nx >> 24) + 1]); }
                const CUtensorMap* const tm = &mp.ld[x >> 24];
                const uint32_t n = x & 255, blk = (z >> 16) & 255, bytes = (z >> 24) << 10, cnt = w >> 24, base = sb + (z & 0xFFFF);
                if (x & (F_SKIP << 16)) {
                    r.slot += n;
                    if (r.slot >= NSLOT) { r.slot -= NSLOT; r.par ^= 1; }
                    continue;
                }
                uint32_t kl;
                {
                    const uint32_t a = (y >> 2) & 63, step = (y >> 16) & 255, ch = a + lane * (step >> 5), u = ch >> 1, q = u < 7 ? u : u - 7;
                    kl = (y & 3) == K_PANEL ? (q + (q >= j)) * 128 + (u < 7 ? 0 : 64) + (ch & 1) * 32
                                            : ch * 32 + ((lane * ((x >> 8) & 255)) >> 7) * (y >> 24) * 64 + ((y & 3) == K_OWN ? kown : 0);
                    kl += (y >> 8) & 48;
                }
                uint32_t wrap = NSLOT - ((x >> 16) & F_WRAP);
                auto acquire = [&](uint32_t& st, uint32_t& fb) {
                    mbar_wait(BAR_EMPTY(sb, r.slot), r.par);
                    st = base + r.slot * SLOT; fb = BAR_FULL(sb, r.slot);
                    if (++r.slot == wrap) { r.slot = 0; r.par ^= 1; }
                    wrap = NSLOT;
                };
                uint32_t st, fb;
                if (w & 0xFFFF) { mbar_wait(sb + OFF_BAR + (w & 0xFFF8), w & 1); fence_async_global(); }
                if (act | aux) {
                    const uint32_t* const fl = g_flags + m * 64 + cnt * 16 + ((kl >> 6) & 15);
                    const int row = (x >> 24) == L_X ? m * 64 : m * 128;
                    uint32_t ready = cnt ? 0 : ~0u;
                    auto need = [&](uint32_t i, uint32_t bits) {
                        while (!((ready >> i) & 1)) {
                            uint32_t v; asm volatile("ld.relaxed.gpu.global.u32 %0, [%1];" : "=r"(v) : "l"(fl) : "memory");
                            ready = __ballot_sync(0xffffffffu, ((v + 3 - 3 * ep) & bits) == bits);
                            fence_async_global();
                        }
                    };
                    if (x & (F_EARLY << 16)) {
                        const uint32_t k0 = __shfl_sync(0xffffffffu, kl, 0), k2 = __shfl_sync(0xffffffffu, kl, 2);
#pragma unroll
                        for (int e = 0; e < 3; ++e) mbar_wait(BAR_FULL(sb, e), 0);
#pragma unroll 1
                        for (int g = 1; g >= 0; --g) {
                            ready = 0;
#pragma unroll
                            for (int e = 0; e < 4; ++e) {
                                if (!(e & 1)) need(e, 3 - 2 * g);
                                fb = g ? BAR_FULL(sb, e ? e - 1 : 4) : BAR_ONE(sb, EV_A0 + e);
                                if (el) { mbar_expect_tx(fb, 4096); tma_load4(sb + (e ? e - 1 : 4) * SLOT + g * 4096, tm + 1, (e < 2 ? k0 : k2) + (e & 1) * 32, row + g * 64, 0, fb); }
                            }
                        }
                        if (el) mbar_arrive(BAR_ONE(sb, EV_SEC));
                        r.slot = 3; r.par ^= 1;
                    }
#pragma unroll 1
                    for (uint32_t i = (x >> 17) & 4; i < n; ++i) {
                        const uint32_t k = __shfl_sync(0xffffffffu, kl, i);
                        need(i, 3);
                        acquire(st, fb);
                        if (el) { mbar_expect_tx(fb, bytes); tma_load4(st, tm, aux ? 0 : k, aux ? k : row, aux ? blk : 0, fb); }
                    }
                } else {
                    const bool twice = el && (x & (F_TWICE << 16)), wd = (x >> 24) == L_WD;
                    const uint32_t more = (x >> 25) == L_WG / 2 ? (bytes >> 13) - 1 : 0;
#pragma unroll 1
                    for (uint32_t i = 0; i < n; ++i) {
                        const uint32_t k = __shfl_sync(0xffffffffu, kl, i);
                        acquire(st, fb);
                        if (twice) mbar_arrive(fb);
                        if (el) { mbar_expect_tx(fb, bytes); tma_load5_mc(st, tm, wd ? blk * 64 : 0, wd ? 0 : k, wd ? 0 : blk, (x >> 24) == L_WKV, wd ? k >> 5 : 0, fb); }
                        if (more && el) tma_load5_mc(st + 8192, tm, 0, k, blk + 1, 0, 0, fb);
                        if (more > 1 && el) tma_load5_mc(st + 16384, tm, 0, k, blk + 2, 0, 0, fb);
                    }
                }
            }
        } else if (!aux) {
            const uint32_t w = warp - 9;
            uint32_t bpar = 0;
            auto send = [&](int t) {
                const CUtensorMap* const tm = t ? &mp.os : &mp.h1s;
                const bool ring = t != 1;
                const uint32_t src = sb + (ring ? OFF_OWN : OFF_STG), par = t & 1;
#pragma unroll 1
                for (uint32_t u = w ? 0 : 1; u < (w ? 1 : 3); ++u) {
                    const uint32_t p = u >> 1, g1 = !(ring && u == 1), g0 = u == 0;
                    if (p && ring) mbar_wait_b(BAR_ONE(sb, EV_SEC), t >> 1);
                    const int col = kown + p * 64, row = m * 128 + g0 * 64;
                    const uint32_t back = BAR_ONE(sb, EV_BACK + w), from = src + p * 16384;
                    if (g1 != g0) {
                        mbar_wait_b(BAR_SFULL(sb, 2 + p), par);
                        if (el) { fence_async_smem(); tma_store(tm, col, row + 64, from + 8192); }
                    }
                    mbar_wait_b(BAR_SFULL(sb, 2 * g0 + p), par);
                    if (el) {
                        fence_async_smem();
                        tma_store(tm, col, row, from + g0 * 8192);
                        bulk_commit();
                        mbar_expect_tx(back, 2048);
                        bulk_wait_all();
#pragma unroll
                        for (int i = 0; i < 4; ++i) tma_load(sb + OFF_JUNK, tm + 2, col, row + (i & 1) * 32 + (i >> 1) * (g1 - g0) * 64, back);
                    }
                    __syncwarp();
                    if (p && ring) {
                        mbar_wait_b(BAR_FULL(sb, 5), 0); mbar_wait_b(BAR_ONE(sb, EV_BACK + 1), t >> 1);
                        if (lane < 4) asm volatile("{\n.reg .b32 r;\nmapa.shared::cluster.u32 r, %0, %1;\nmbarrier.arrive.shared::cluster.b64 _, [r];\n}" :: "r"(BAR_EMPTY(sb, 5)), "r"(lane & 1) : "memory");
                    }
                    mbar_wait_b(back, bpar);
                    bpar ^= 1;
                    if (el) asm volatile("red.relaxed.gpu.global.add.u32 [%0], %1;" :: "l"(g_flags + m * 64 + 16 + t * 16 + 2 * j + p), "r"(g1 + 2 - 2 * g0) : "memory");
                }
            };
            auto gate = [&](int vec, int ev) {
                uint2 a, b; uint32_t n = 0;
                const uint2* src = g_mod + vec * 512 + j * 64 + (lane >> 2) * 8 + (lane & 3);
                while (true) {
                    a = ld_pkt(src); b = ld_pkt(src + 4);
                    if (__all_sync(0xffffffffu, a.y == ep && b.y == ep)) break;
                    SPIN_GUARD(n); __nanosleep(300);
                }
                sts128(sb + OFF_TAB + (ev - EV_GA) * 512 + lane * 16, a.x << 16, a.x & 0xFFFF0000u, b.x << 16, b.x & 0xFFFF0000u);
                __syncwarp();
                if (el) mbar_arrive(BAR_ONE(sb, ev));
            };
            if (lane < 6) prefetch_map(lane < 4 ? &mp.h1s + lane : &mp.ld[L_H1 - 4 + lane]);
            auto count = [&](int f) {
                uint32_t v, n = 0;
                while (true) {
                    asm volatile("ld.acquire.gpu.global.u32 %0, [%1];" : "=r"(v) : "l"(g_flags + f) : "memory");
                    if ((int32_t)(v - ep * 8) >= 0) break;
                    SPIN_GUARD(n); __nanosleep(500);
                }
            };
#pragma unroll 1
            for (int t = 0; t < 3; t += 1 + w) {
                send(t);
                if (w == 0) {
                    if (t && el) mbar_arrive(BAR_ONE(sb, t == 1 ? EV_P2 : EV_SENT));
                    if (t == 1 && m > 0) {
#pragma unroll 4
                        for (int i = 0; i < 16; ++i) (g_halo + ((m - 1) * 8 + j) * 512 + lane)[i * 32] = make_uint4(0, 0, 0, 0);
                    }
                } else {
                    gate(t ? 5 : 2, t ? EV_GB : EV_GA);
                    if (t == 0) {
                        count(FL_LN2);
                        const uint4 v = __ldcg((const uint4*)(g_par2 + j * 128) + lane);
                        mbar_wait_b(BAR_SFULL(sb, 2), 1);
                        sts128(sb + OFF_PAR + lane * 16, v.x, v.y, v.z, v.w);
                        __syncwarp();
                        if (el) mbar_arrive(BAR_ONE(sb, EV_P2));
                    }
                }
            }
            if (!w && el) flag_add(g_flags + FL_DONE);
            if (w) {
#pragma unroll 1
                for (int p = 0; p < 3; ++p) {
                    mbar_wait_b(BAR_ONE(sb, EV_HB), p & 1);
                    __nanosleep(RESTH);
                    if (el) asm volatile("red.release.gpu.global.add.u32 [%0], 1;" :: "l"(g_flags + m * 64 + p) : "memory");
                    count(m * 64 + p);
                    if (el) mbar_arrive(BAR_ONE(sb, EV_H + p));
                }
            }
            cluster_arrive_early = true;
            cluster_arrive();
            mbar_wait_b(BAR_SFULL(sb, w * 2), 1);
        }
        __syncwarp();
    }
    if (aux || (wg == 2 && !cluster_arrive_early)) cluster_arrive();
    cluster_wait();
    bulk_wait_read();
    if (tid == 0) {
        if (aux) flag_add(pt.mail->flags + FL_DONE);
    }
}

typedef CUresult (*EncodeFn)(CUtensorMap*, CUtensorMapDataType, cuuint32_t, void*, const cuuint64_t*, const cuuint64_t*, const cuuint32_t*,
                             const cuuint32_t*, CUtensorMapInterleave, CUtensorMapSwizzle, CUtensorMapL2promotion, CUtensorMapFloatOOBfill);

void make_map(EncodeFn fn, CUtensorMap* m, const void* ptr, uint64_t rows, uint64_t cols, uint32_t brows, uint32_t bcols) {
    cuuint64_t dims[2] = {cols, rows}, strides[1] = {cols * 2};
    cuuint32_t box[2] = {bcols, brows}, es[2] = {1, 1};
    fn(m, CU_TENSOR_MAP_DATA_TYPE_BFLOAT16, 2, (void*)ptr, dims, strides, box, es, CU_TENSOR_MAP_INTERLEAVE_NONE,
       bcols == 64 ? CU_TENSOR_MAP_SWIZZLE_128B : bcols == 32 ? CU_TENSOR_MAP_SWIZZLE_64B : CU_TENSOR_MAP_SWIZZLE_NONE,
       bcols == 8 ? CU_TENSOR_MAP_L2_PROMOTION_NONE : CU_TENSOR_MAP_L2_PROMOTION_L2_128B, CU_TENSOR_MAP_FLOAT_OOB_FILL_NONE);
}
struct View { uint64_t dim[5], stride[4]; uint32_t box[5]; };
void make_view(EncodeFn fn, CUtensorMap* m, const void* ptr, uint32_t rank, const View& v) {
    cuuint64_t dims[5], strides[4];
    cuuint32_t box[5], es[5] = {1, 1, 1, 1, 1};
    for (int i = 0; i < 5; ++i) { dims[i] = v.dim[i]; box[i] = v.box[i]; if (i < 4) strides[i] = v.stride[i] * 2; }
    fn(m, CU_TENSOR_MAP_DATA_TYPE_BFLOAT16, rank, (void*)ptr, dims, strides, box, es, CU_TENSOR_MAP_INTERLEAVE_NONE,
       box[0] == 64 ? CU_TENSOR_MAP_SWIZZLE_128B : CU_TENSOR_MAP_SWIZZLE_64B, CU_TENSOR_MAP_L2_PROMOTION_L2_128B, CU_TENSOR_MAP_FLOAT_OOB_FILL_NONE);
}

}

extern "C" void kernel_launch(void* const* d_in, const int* in_sizes, int n_in, void* d_out, int out_size) {
    (void)in_sizes; (void)n_in; (void)out_size;
    void* fnp = nullptr;
    cudaDriverEntryPointQueryResult qr;
    cudaGetDriverEntryPoint("cuTensorMapEncodeTiled", &fnp, cudaEnableDefault, &qr);
    EncodeFn fn = (EncodeFn)fnp;
    void *h1, *o, *hb, *mail, *sched;
    cudaGetSymbolAddress(&h1, g_h1);
    cudaGetSymbolAddress(&mail, g_mail);
    cudaGetSymbolAddress(&o, g_o);
    cudaGetSymbolAddress(&hb, g_hb);
    cudaGetSymbolAddress(&sched, g_sched);
    Maps mp;
    auto wmap = [&](int i, const void* p, uint64_t rows, uint64_t cols, uint64_t sec, uint32_t brows, uint32_t bblk, uint32_t bsec) {
        make_view(fn, &mp.ld[i], p, i == L_WMOD ? 4 : 5, View{{64, rows, cols / sec / 64, sec, 1}, {cols, 64, cols / sec, 64}, {64, brows, bblk, bsec, 1}});
    };
    auto amap = [&](int i, const void* p, uint64_t cols, uint32_t bcols, uint32_t brows = 128) { make_view(fn, &mp.ld[i], p, 4, View{{cols, S_, 1, 1, 1}, {cols, 64, 64, 64}, {bcols, brows, 1, 1, 1}}); };
    wmap(L_WQKV, d_in[1], D_, 3 * D_, 3, 16, 2, 3);
    wmap(L_WKV, d_in[1], D_, 3 * D_, 3, 16, 2, 2);
    wmap(L_WQ, d_in[1], D_, 3 * D_, 3, 64, 1, 1);
    wmap(L_WQ1, d_in[1], D_, 3 * D_, 3, 32, 1, 1);
    wmap(L_WO, d_in[2], D_, D_, 1, 64, 1, 1);
    wmap(L_WG, d_in[4], D_, F_, 1, 32, 1, 1);
    wmap(L_WU, d_in[5], D_, F_, 1, 32, 1, 1);
    make_view(fn, &mp.ld[L_WD], d_in[6], 5, View{{D_, 2, 4, 4, F_ / 32}, {D_, 8 * D_, 2 * D_, 32 * D_}, {64, 2, 4, 4, 2}});
    wmap(L_WMOD, d_in[8], D_, 6 * D_, 1, 64, 4, 1);
    amap(L_H1, h1, D_, 32); amap(L_H1Q, h1, D_, 64); amap(L_O, o, D_, 64); amap(L_H2, o, D_, 32); amap(L_HB, hb, F_, 64);
    amap(L_H1E, h1, D_, 32, 64); amap(L_H2E, o, D_, 32, 64);
    make_view(fn, &mp.ld[L_X], d_in[0], 4, View{{D_, S_ / 2, 2, 1, 1}, {2 * D_, D_, 64, 64}, {64, 64, 2, 1, 1}});
    make_map(fn, &mp.h1s, h1, S_, D_, 64, 64);
    make_map(fn, &mp.os, o, S_, D_, 64, 64);
    make_map(fn, &mp.h1r, h1, S_, D_, 32, 8);
    make_map(fn, &mp.orr, o, S_, D_, 32, 8);
    make_map(fn, &mp.wm, d_in[8], D_, 6 * D_, 64, 64);
    make_map(fn, &mp.x, d_in[0], S_ / 2, 2 * D_, 64, 64);
    make_map(fn, &mp.out, d_out, S_ / 2, 2 * D_, 8, 64);
    cudaFuncSetAttribute(fused_block_kernel, cudaFuncAttributeMaxDynamicSharedMemorySize, SMEM_BYTES);
    cudaLaunchConfig_t cfg = {};
    cfg.gridDim = dim3(NCTA); cfg.blockDim = dim3(384); cfg.dynamicSmemBytes = SMEM_BYTES; cfg.stream = cudaStreamPerThread;
    cudaLaunchAttribute at[1];
    at[0].id = cudaLaunchAttributeClusterDimension; at[0].val.clusterDim.x = 2; at[0].val.clusterDim.y = 1; at[0].val.clusterDim.z = 1;
    cfg.attrs = at; cfg.numAttrs = 1;
    const Ptrs pt{(const __nv_bfloat16*)d_in[7], (Mail*)mail, (__nv_bfloat16*)hb, (const uint4*)sched, (const __nv_bfloat16*)d_in[0]};
    cudaLaunchKernelEx(&cfg, fused_block_kernel, pt, mp);
}
```

```cpp
#include <cuda_runtime.h>
#include <cuda_bf16.h>
#include <cuda.h>
#include <stdint.h>
#include <stddef.h>

constexpr int LAG = 3;
constexpr int LAGS = 2;
constexpr int LAGW = 4;
constexpr int LAGD = 3;
constexpr int LAGQ = 3;
constexpr int LAGX = 4;
constexpr int EARLY = 1;
constexpr int NQ = 6;
constexpr int NS = 5;
constexpr int RC = 224;
constexpr int RESTH = 300;
constexpr int NB0 = 2;
constexpr int NB1 = 3;
constexpr int GW = 4;
constexpr int GD = 0;
constexpr int SWO = 2;
constexpr int QA = 3;

namespace {

constexpr int S_ = 2048, D_ = 1024, F_ = 3584;
constexpr int NCTA = 132;
constexpr int NSLOT = 6;
constexpr uint32_t SLOT = 32768;
constexpr uint32_t OFF_STG = NSLOT * SLOT;
constexpr uint32_t OFF_BAR = OFF_STG + 32768;
constexpr uint32_t OFF_PAR = OFF_BAR + 384;
constexpr uint32_t OFF_TAB = OFF_PAR + 512;
constexpr uint32_t OFF_JUNK = 0u - 1024;
constexpr uint32_t SMEM_BYTES = 1024 + OFF_TAB + 1024;
constexpr int ST_Q = 33, ST_WO = ST_Q + NQ + NS, ST_GU = ST_WO + 16, ST_G1 = ST_GU + 33;
static_assert(ST_GU % (2 * NSLOT) == 0, "");
constexpr uint32_t OFF_OWN = 5 * SLOT;
constexpr uint32_t sweep_order() {
    uint32_t v = 0, n = 0;
    for (uint32_t hi = 0; hi < 2; ++hi)
        for (int i = 0; i < NS; ++i) { const uint32_t t = ST_WO - NS + i, s = t % NSLOT; if ((s >= 4) == hi) v |= (s | (t / NSLOT & 1) << 3) << (4 * n++); }
    return v;
}
constexpr uint32_t SWEEP = sweep_order();

constexpr int FL_DONE = 16 * 64, FL_LN2 = 16 * 64 + 1, FL_WX = 16 * 64 + 2;

enum { L_WQKV, L_WKV, L_WQ, L_WO, L_WG, L_WU, L_WGX, L_WUX, L_WD, L_WD3, L_WQ1, L_WMOD, L_H1, L_H1E, L_H1Q, L_X, L_O, L_H2, L_H2E, L_HB, L_COUNT };
struct Maps {
    CUtensorMap wm, x, h1s, os, h1r, orr, ld[L_COUNT], out;
};

struct Mail {
    uint32_t flags[16 * 64 + 32];
    uint2 mod[6 * D_ / 2];
    uint4 mod1[8 * 2048];
    uint4 st1[8 * S_ / 2];
    uint32_t par2[D_];
    uint4 halo[128 * 512];
};
struct Ptrs { const __nv_bfloat16* c; Mail* mail; __nv_bfloat16* hb; const uint4* sched; const __nv_bfloat16 *x, *wg, *wu; __nv_bfloat16* wx; };

__device__ __align__(128) Mail g_mail;
__device__ __align__(128) __nv_bfloat16 g_h1[S_ * D_];
__device__ __align__(128) __nv_bfloat16 g_o[S_ * D_];
__device__ __align__(128) __nv_bfloat16 g_wx[2 * D_ * 128];
__device__ __align__(128) __nv_bfloat16 g_hb[S_ * F_];

__device__ __forceinline__ uint32_t smem_u32(const void* p) { return (uint32_t)__cvta_generic_to_shared(p); }
__device__ __forceinline__ void mbar_init(uint32_t bar, uint32_t cnt) { asm volatile("mbarrier.init.shared::cta.b64 [%0], %1;" :: "r"(bar), "r"(cnt) : "memory"); }
__device__ __forceinline__ void mbar_expect_tx(uint32_t bar, uint32_t bytes) { asm volatile("mbarrier.arrive.expect_tx.shared::cta.b64 _, [%0], %1;" :: "r"(bar), "r"(bytes) : "memory"); }
__device__ __forceinline__ void mbar_arrive(uint32_t bar) { asm volatile("mbarrier.arrive.shared::cta.b64 _, [%0];" :: "r"(bar) : "memory"); }
__device__ __forceinline__ void mbar_arrive_if0(uint32_t bar, uint32_t z) {
    asm volatile("{\n.reg .pred p;\nsetp.eq.u32 p, %1, 0;\n@p mbarrier.arrive.shared::cta.b64 _, [%0];\n}" :: "r"(bar), "r"(z) : "memory");
}
__device__ __forceinline__ void mbar_wait(uint32_t bar, uint32_t parity) {
    asm volatile("{\n.reg .pred p;\nW_LOOP:\nmbarrier.try_wait.parity.shared::cta.b64 p, [%0], %1;\n@!p bra W_LOOP;\n}" :: "r"(bar), "r"(parity) : "memory");
}
__device__ __forceinline__ void mbar_wait_b(uint32_t bar, uint32_t parity) {
    asm volatile("{\n.reg .pred p;\n.reg .u32 n;\nmov.u32 n, 0;\n"
        "W_LOOP:\nmbarrier.try_wait.parity.shared::cta.b64 p, [%0], %1;\n@p bra W_DONE;\n"
        "add.u32 n, n, 1;\nsetp.lt.u32 p, n, 0x400000;\n@p bra W_LOOP;\ntrap;\nW_DONE:\n}" :: "r"(bar), "r"(parity) : "memory");
}
__device__ __forceinline__ void tma_load(uint32_t dst, const CUtensorMap* m, int c0, int c1, uint32_t bar) {
    asm volatile("cp.async.bulk.tensor.2d.shared::cluster.global.mbarrier::complete_tx::bytes [%0], [%1, {%3, %4}], [%2];"
        :: "r"(dst), "l"(m), "r"(bar), "r"(c0), "r"(c1) : "memory");
}
__device__ __forceinline__ void tma_load4(uint32_t dst, const CUtensorMap* m, int c0, int c1, int c2, uint32_t bar) {
    asm volatile("cp.async.bulk.tensor.4d.shared::cluster.global.mbarrier::complete_tx::bytes [%0], [%1, {%3, %4, %5, %6}], [%2];"
        :: "r"(dst), "l"(m), "r"(bar), "r"(c0), "r"(c1), "r"(c2), "r"(0) : "memory");
}
__device__ __forceinline__ void tma_load5_mc(uint32_t dst, const CUtensorMap* m, int c0, int c1, int c2, int c3, int c4, uint32_t bar) {
    asm volatile("cp.async.bulk.tensor.5d.shared::cluster.global.mbarrier::complete_tx::bytes.multicast::cluster.L2::cache_hint [%0], [%1, {%3, %4, %5, %6, %7}], [%2], %8, %9;"
        :: "r"(dst), "l"(m), "r"(bar), "r"(c0), "r"(c1), "r"(c2), "r"(c3), "r"(c4), "h"((uint16_t)3), "l"(0x12F0000000000000ull) : "memory");
}
__device__ __forceinline__ void tma_store(const CUtensorMap* m, int c0, int c1, uint32_t src) {
    asm volatile("cp.async.bulk.tensor.2d.global.shared::cta.bulk_group [%0, {%2, %3}], [%1];" :: "l"(m), "r"(src), "r"(c0), "r"(c1) : "memory");
}
__device__ __forceinline__ void bulk_commit() { asm volatile("cp.async.bulk.commit_group;" ::: "memory"); }
__device__ __forceinline__ void bulk_wait_read() { asm volatile("cp.async.bulk.wait_group.read 0;" ::: "memory"); }
__device__ __forceinline__ void bulk_wait_all() { asm volatile("cp.async.bulk.wait_group 0;" ::: "memory"); }
__device__ __forceinline__ void fence_async_smem() { asm volatile("fence.proxy.async.shared::cta;" ::: "memory"); }
__device__ __forceinline__ void fence_async_global() { asm volatile("fence.proxy.async.global;" ::: "memory"); }
__device__ __forceinline__ void prefetch_map(const CUtensorMap* m) { asm volatile("prefetch.tensormap [%0];" :: "l"(m) : "memory"); }
__device__ __forceinline__ void wg_fence() { asm volatile("wgmma.fence.sync.aligned;" ::: "memory"); }
__device__ __forceinline__ void wg_commit() { asm volatile("wgmma.commit_group.sync.aligned;" ::: "memory"); }
template <int N> __device__ __forceinline__ void wg_wait() { asm volatile("wgmma.wait_group.sync.aligned %0;" :: "n"(N) : "memory"); }
__device__ __forceinline__ void bar_sync(int id, int n) { asm volatile("bar.sync %0, %1;" :: "r"(id), "r"(n) : "memory"); }
__device__ __forceinline__ void flag_add(uint32_t* f) { asm volatile("red.relaxed.gpu.global.add.u32 [%0], 1;" :: "l"(f) : "memory"); }
__device__ __forceinline__ uint32_t d16(uint32_t addr) { return (addr & 0x3FFFF) >> 4; }
__device__ __forceinline__ uint64_t mk_desc(uint32_t a16, uint32_t off, uint32_t lbo, uint32_t sbo, uint32_t swz) {
    const uint32_t lo = a16 + (off >> 4) + ((lbo >> 4) << 16), hi = (sbo >> 4) | (swz << 30);
    return ((uint64_t)hi << 32) | lo;
}
__device__ __forceinline__ uint32_t pack2(float lo, float hi) {
    uint32_t r; asm("cvt.rn.bf16x2.f32 %0, %1, %2;" : "=r"(r) : "f"(hi), "f"(lo)); return r;
}
__device__ __forceinline__ uint32_t hfma2_bf16(uint32_t a, uint32_t b, uint32_t c) {
    uint32_t r; asm("fma.rn.bf16x2 %0, %1, %2, %3;" : "=r"(r) : "r"(a), "r"(b), "r"(c)); return r;
}
__device__ __forceinline__ float bf_lo(uint32_t v) { return __uint_as_float(v << 16); }
__device__ __forceinline__ float bf_hi(uint32_t v) { return __uint_as_float(v & 0xFFFF0000u); }
__device__ __forceinline__ float bf_round(float x) { return __bfloat162float(__float2bfloat16_rn(x)); }
__device__ __forceinline__ void stsm4(uint32_t addr, uint32_t r0, uint32_t r1, uint32_t r2, uint32_t r3) {
    asm volatile("stmatrix.sync.aligned.m8n8.x4.shared.b16 [%0], {%1, %2, %3, %4};" :: "r"(addr), "r"(r0), "r"(r1), "r"(r2), "r"(r3) : "memory");
}
__device__ __forceinline__ void stsm4t(uint32_t addr, uint32_t r0, uint32_t r1, uint32_t r2, uint32_t r3) {
    asm volatile("stmatrix.sync.aligned.m8n8.x4.trans.shared.b16 [%0], {%1, %2, %3, %4};" :: "r"(addr), "r"(r0), "r"(r1), "r"(r2), "r"(r3) : "memory");
}
__device__ __forceinline__ void ldsm4(uint32_t addr, uint32_t& r0, uint32_t& r1, uint32_t& r2, uint32_t& r3) {
    asm volatile("ldmatrix.sync.aligned.m8n8.x4.shared.b16 {%0, %1, %2, %3}, [%4];" : "=r"(r0), "=r"(r1), "=r"(r2), "=r"(r3) : "r"(addr) : "memory");
}
__device__ __forceinline__ uint32_t movm(uint32_t a) { uint32_t r; asm volatile("movmatrix.sync.aligned.m8n8.trans.b16 %0, %1;" : "=r"(r) : "r"(a)); return r; }
__device__ __forceinline__ void mma16816(float (&c)[4], uint32_t a0, uint32_t a1, uint32_t a2, uint32_t a3, uint32_t b0, uint32_t b1) {
    asm("mma.sync.aligned.m16n8k16.row.col.f32.bf16.bf16.f32 {%0, %1, %2, %3}, {%4, %5, %6, %7}, {%8, %9}, {%0, %1, %2, %3};"
        : "+f"(c[0]), "+f"(c[1]), "+f"(c[2]), "+f"(c[3]) : "r"(a0), "r"(a1), "r"(a2), "r"(a3), "r"(b0), "r"(b1));
}
__device__ __forceinline__ float ex2(float x) { float r; asm("ex2.approx.ftz.f32 %0, %1;" : "=f"(r) : "f"(x)); return r; }
__device__ __forceinline__ float rcp(float x) { float r; asm("rcp.approx.ftz.f32 %0, %1;" : "=f"(r) : "f"(x)); return r; }
__device__ __forceinline__ float rsq(float x) { float r; asm("rsqrt.approx.ftz.f32 %0, %1;" : "=f"(r) : "f"(x)); return r; }
__device__ __forceinline__ float silu_(float x) { return x * rcp(1.f + ex2(-1.4426950408889634f * x)); }
__device__ __forceinline__ void st_pkt(void* p, uint32_t a, uint32_t b) {
    asm volatile("{\n.reg .b64 t;\nmov.b64 t, {%1, %2};\nst.relaxed.gpu.global.b64 [%0], t;\n}" :: "l"(p), "r"(a), "r"(b) : "memory");
}
__device__ __forceinline__ uint2 ld_pkt(const void* p) {
    uint2 v; asm volatile("{\n.reg .b64 t;\nld.relaxed.gpu.global.b64 t, [%2];\nmov.b64 {%0, %1}, t;\n}" : "=r"(v.x), "=r"(v.y) : "l"(p) : "memory"); return v;
}
__device__ __forceinline__ void st_pkt16(void* p, uint32_t a, uint32_t b, uint32_t c, uint32_t d) {
    asm volatile("{\n.reg .b64 t, u;\n.reg .b128 w;\nmov.b64 t, {%1, %2};\nmov.b64 u, {%3, %4};\nmov.b128 w, {t, u};\nst.relaxed.gpu.global.b128 [%0], w;\n}"
        :: "l"(p), "r"(a), "r"(b), "r"(c), "r"(d) : "memory");
}
__device__ __forceinline__ uint4 ld_pkt16(const void* p) {
    uint4 v; asm volatile("{\n.reg .b64 t, u;\n.reg .b128 w;\nld.relaxed.gpu.global.b128 w, [%4];\nmov.b128 {t, u}, w;\nmov.b64 {%0, %1}, t;\nmov.b64 {%2, %3}, u;\n}"
        : "=r"(v.x), "=r"(v.y), "=r"(v.z), "=r"(v.w) : "l"(p) : "memory"); return v;
}
#define SPIN_GUARD(n) do { if (++(n) > (1u << 22)) asm volatile("trap;"); } while (0)
__device__ __forceinline__ uint4 lds128(uint32_t a) { uint4 v; asm volatile("ld.shared.v4.u32 {%0, %1, %2, %3}, [%4];" : "=r"(v.x), "=r"(v.y), "=r"(v.z), "=r"(v.w) : "r"(a) : "memory"); return v; }
__device__ __forceinline__ void sts128(uint32_t a, uint32_t x, uint32_t y, uint32_t z, uint32_t w) { asm volatile("st.shared.v4.u32 [%0], {%1, %2, %3, %4};" :: "r"(a), "r"(x), "r"(y), "r"(z), "r"(w) : "memory"); }
__device__ __forceinline__ uint2 lds64(uint32_t a) { uint2 v; asm volatile("ld.shared.v2.u32 {%0, %1}, [%2];" : "=r"(v.x), "=r"(v.y) : "r"(a) : "memory"); return v; }
__device__ __forceinline__ void sts64(uint32_t a, uint32_t x, uint32_t y) { asm volatile("st.shared.v2.u32 [%0], {%1, %2};" :: "r"(a), "r"(x), "r"(y) : "memory"); }
__device__ __forceinline__ uint32_t lds32(uint32_t a) { uint32_t v; asm volatile("ld.shared.u32 %0, [%1];" : "=r"(v) : "r"(a) : "memory"); return v; }
__device__ __forceinline__ void sts32(uint32_t a, uint32_t v) { asm volatile("st.shared.u32 [%0], %1;" :: "r"(a), "r"(v) : "memory"); }
__device__ __forceinline__ bool elect_one() {
    uint32_t p; asm volatile("{\n.reg .pred q;\nelect.sync _|q, 0xffffffff;\nselp.u32 %0, 1, 0, q;\n}" : "=r"(p)); return p;
}
__device__ __forceinline__ void cluster_arrive() { asm volatile("barrier.cluster.arrive.relaxed.aligned;" ::: "memory"); }
__device__ __forceinline__ void cluster_wait() { asm volatile("barrier.cluster.wait.aligned;" ::: "memory"); }

__device__ __forceinline__ void wgmma_n128(float (&d)[64], uint64_t da, uint64_t db, uint32_t add = 1) {
    asm volatile("{\n.reg .pred p;\nsetp.ne.b32 p, %66, 0;\n"
        "wgmma.mma_async.sync.aligned.m64n128k16.f32.bf16.bf16 {"
        "%0, %1, %2, %3, %4, %5, %6, %7, %8, %9, %10, %11, %12, %13, %14, %15, "
        "%16, %17, %18, %19, %20, %21, %22, %23, %24, %25, %26, %27, %28, %29, %30, %31, "
        "%32, %33, %34, %35, %36, %37, %38, %39, %40, %41, %42, %43, %44, %45, %46, %47, "
        "%48, %49, %50, %51, %52, %53, %54, %55, %56, %57, %58, %59, %60, %61, %62, %63"
        "}, %64, %65, p, 1, 1, 0, 1;\n}\n"
        : "+f"(d[0]), "+f"(d[1]), "+f"(d[2]), "+f"(d[3]), "+f"(d[4]), "+f"(d[5]), "+f"(d[6]), "+f"(d[7]),
          "+f"(d[8]), "+f"(d[9]), "+f"(d[10]), "+f"(d[11]), "+f"(d[12]), "+f"(d[13]), "+f"(d[14]), "+f"(d[15]),
          "+f"(d[16]), "+f"(d[17]), "+f"(d[18]), "+f"(d[19]), "+f"(d[20]), "+f"(d[21]), "+f"(d[22]), "+f"(d[23]),
          "+f"(d[24]), "+f"(d[25]), "+f"(d[26]), "+f"(d[27]), "+f"(d[28]), "+f"(d[29]), "+f"(d[30]), "+f"(d[31]),
          "+f"(d[32]), "+f"(d[33]), "+f"(d[34]), "+f"(d[35]), "+f"(d[36]), "+f"(d[37]), "+f"(d[38]), "+f"(d[39]),
          "+f"(d[40]), "+f"(d[41]), "+f"(d[42]), "+f"(d[43]), "+f"(d[44]), "+f"(d[45]), "+f"(d[46]), "+f"(d[47]),
          "+f"(d[48]), "+f"(d[49]), "+f"(d[50]), "+f"(d[51]), "+f"(d[52]), "+f"(d[53]), "+f"(d[54]), "+f"(d[55]),
          "+f"(d[56]), "+f"(d[57]), "+f"(d[58]), "+f"(d[59]), "+f"(d[60]), "+f"(d[61]), "+f"(d[62]), "+f"(d[63])
        : "l"(da), "l"(db), "r"(add));
}
__device__ __forceinline__ void wgmma_n176(float (&d)[88], uint64_t da, uint64_t db, uint32_t add = 1) {
    asm volatile("{\n.reg .pred p;\nsetp.ne.b32 p, %90, 0;\n"
        "wgmma.mma_async.sync.aligned.m64n176k16.f32.bf16.bf16 {"
        "%0, %1, %2, %3, %4, %5, %6, %7, %8, %9, %10, %11, %12, %13, %14, %15, "
        "%16, %17, %18, %19, %20, %21, %22, %23, %24, %25, %26, %27, %28, %29, %30, %31, "
        "%32, %33, %34, %35, %36, %37, %38, %39, %40, %41, %42, %43, %44, %45, %46, %47, "
        "%48, %49, %50, %51, %52, %53, %54, %55, %56, %57, %58, %59, %60, %61, %62, %63, "
        "%64, %65, %66, %67, %68, %69, %70, %71, %72, %73, %74, %75, %76, %77, %78, %79, "
        "%80, %81, %82, %83, %84, %85, %86, %87"
        "}, %88, %89, p, 1, 1, 0, 1;\n}\n"
        : "+f"(d[0]), "+f"(d[1]), "+f"(d[2]), "+f"(d[3]), "+f"(d[4]), "+f"(d[5]), "+f"(d[6]), "+f"(d[7]),
          "+f"(d[8]), "+f"(d[9]), "+f"(d[10]), "+f"(d[11]), "+f"(d[12]), "+f"(d[13]), "+f"(d[14]), "+f"(d[15]),
          "+f"(d[16]), "+f"(d[17]), "+f"(d[18]), "+f"(d[19]), "+f"(d[20]), "+f"(d[21]), "+f"(d[22]), "+f"(d[23]),
          "+f"(d[24]), "+f"(d[25]), "+f"(d[26]), "+f"(d[27]), "+f"(d[28]), "+f"(d[29]), "+f"(d[30]), "+f"(d[31]),
          "+f"(d[32]), "+f"(d[33]), "+f"(d[34]), "+f"(d[35]), "+f"(d[36]), "+f"(d[37]), "+f"(d[38]), "+f"(d[39]),
          "+f"(d[40]), "+f"(d[41]), "+f"(d[42]), "+f"(d[43]), "+f"(d[44]), "+f"(d[45]), "+f"(d[46]), "+f"(d[47]),
          "+f"(d[48]), "+f"(d[49]), "+f"(d[50]), "+f"(d[51]), "+f"(d[52]), "+f"(d[53]), "+f"(d[54]), "+f"(d[55]),
          "+f"(d[56]), "+f"(d[57]), "+f"(d[58]), "+f"(d[59]), "+f"(d[60]), "+f"(d[61]), "+f"(d[62]), "+f"(d[63]),
          "+f"(d[64]), "+f"(d[65]), "+f"(d[66]), "+f"(d[67]), "+f"(d[68]), "+f"(d[69]), "+f"(d[70]), "+f"(d[71]),
          "+f"(d[72]), "+f"(d[73]), "+f"(d[74]), "+f"(d[75]), "+f"(d[76]), "+f"(d[77]), "+f"(d[78]), "+f"(d[79]),
          "+f"(d[80]), "+f"(d[81]), "+f"(d[82]), "+f"(d[83]), "+f"(d[84]), "+f"(d[85]), "+f"(d[86]), "+f"(d[87])
        : "l"(da), "l"(db), "r"(add));
}
__device__ __forceinline__ void wgmma_n256(float (&d)[128], uint64_t da, uint64_t db, uint32_t add = 1) {
    asm volatile("{\n.reg .pred p;\nsetp.ne.b32 p, %130, 0;\n"
        "wgmma.mma_async.sync.aligned.m64n256k16.f32.bf16.bf16 {"
        "%0, %1, %2, %3, %4, %5, %6, %7, %8, %9, %10, %11, %12, %13, %14, %15, "
        "%16, %17, %18, %19, %20, %21, %22, %23, %24, %25, %26, %27, %28, %29, %30, %31, "
        "%32, %33, %34, %35, %36, %37, %38, %39, %40, %41, %42, %43, %44, %45, %46, %47, "
        "%48, %49, %50, %51, %52, %53, %54, %55, %56, %57, %58, %59, %60, %61, %62, %63, "
        "%64, %65, %66, %67, %68, %69, %70, %71, %72, %73, %74, %75, %76, %77, %78, %79, "
        "%80, %81, %82, %83, %84, %85, %86, %87, %88, %89, %90, %91, %92, %93, %94, %95, "
        "%96, %97, %98, %99, %100, %101, %102, %103, %104, %105, %106, %107, %108, %109, %110, %111, "
        "%112, %113, %114, %115, %116, %117, %118, %119, %120, %121, %122, %123, %124, %125, %126, %127"
        "}, %128, %129, p, 1, 1, 0, 1;\n}\n"
        : "+f"(d[0]), "+f"(d[1]), "+f"(d[2]), "+f"(d[3]), "+f"(d[4]), "+f"(d[5]), "+f"(d[6]), "+f"(d[7]),
          "+f"(d[8]), "+f"(d[9]), "+f"(d[10]), "+f"(d[11]), "+f"(d[12]), "+f"(d[13]), "+f"(d[14]), "+f"(d[15]),
          "+f"(d[16]), "+f"(d[17]), "+f"(d[18]), "+f"(d[19]), "+f"(d[20]), "+f"(d[21]), "+f"(d[22]), "+f"(d[23]),
          "+f"(d[24]), "+f"(d[25]), "+f"(d[26]), "+f"(d[27]), "+f"(d[28]), "+f"(d[29]), "+f"(d[30]), "+f"(d[31]),
          "+f"(d[32]), "+f"(d[33]), "+f"(d[34]), "+f"(d[35]), "+f"(d[36]), "+f"(d[37]), "+f"(d[38]), "+f"(d[39]),
          "+f"(d[40]), "+f"(d[41]), "+f"(d[42]), "+f"(d[43]), "+f"(d[44]), "+f"(d[45]), "+f"(d[46]), "+f"(d[47]),
          "+f"(d[48]), "+f"(d[49]), "+f"(d[50]), "+f"(d[51]), "+f"(d[52]), "+f"(d[53]), "+f"(d[54]), "+f"(d[55]),
          "+f"(d[56]), "+f"(d[57]), "+f"(d[58]), "+f"(d[59]), "+f"(d[60]), "+f"(d[61]), "+f"(d[62]), "+f"(d[63]),
          "+f"(d[64]), "+f"(d[65]), "+f"(d[66]), "+f"(d[67]), "+f"(d[68]), "+f"(d[69]), "+f"(d[70]), "+f"(d[71]),
          "+f"(d[72]), "+f"(d[73]), "+f"(d[74]), "+f"(d[75]), "+f"(d[76]), "+f"(d[77]), "+f"(d[78]), "+f"(d[79]),
          "+f"(d[80]), "+f"(d[81]), "+f"(d[82]), "+f"(d[83]), "+f"(d[84]), "+f"(d[85]), "+f"(d[86]), "+f"(d[87]),
          "+f"(d[88]), "+f"(d[89]), "+f"(d[90]), "+f"(d[91]), "+f"(d[92]), "+f"(d[93]), "+f"(d[94]), "+f"(d[95]),
          "+f"(d[96]), "+f"(d[97]), "+f"(d[98]), "+f"(d[99]), "+f"(d[100]), "+f"(d[101]), "+f"(d[102]), "+f"(d[103]),
          "+f"(d[104]), "+f"(d[105]), "+f"(d[106]), "+f"(d[107]), "+f"(d[108]), "+f"(d[109]), "+f"(d[110]), "+f"(d[111]),
          "+f"(d[112]), "+f"(d[113]), "+f"(d[114]), "+f"(d[115]), "+f"(d[116]), "+f"(d[117]), "+f"(d[118]), "+f"(d[119]),
          "+f"(d[120]), "+f"(d[121]), "+f"(d[122]), "+f"(d[123]), "+f"(d[124]), "+f"(d[125]), "+f"(d[126]), "+f"(d[127])
        : "l"(da), "l"(db), "r"(add));
}
template <int O, int L>
__device__ __forceinline__ void wgmma_n64(float (&d)[L], uint64_t da, uint64_t db) {
    asm volatile("{\n.reg .pred p;\nsetp.eq.b32 p, 0, 0;\n"
        "wgmma.mma_async.sync.aligned.m64n64k16.f32.bf16.bf16 {%0, %1, %2, %3, %4, %5, %6, %7, %8, %9, %10, %11, %12, %13, %14, %15, %16, %17, %18, %19, %20, %21, %22, %23, %24, %25, %26, %27, %28, %29, %30, %31}, %32, %33, p, 1, 1, 0, 1;\n}\n"
        : "+f"(d[O + 0]), "+f"(d[O + 1]), "+f"(d[O + 2]), "+f"(d[O + 3]), "+f"(d[O + 4]), "+f"(d[O + 5]), "+f"(d[O + 6]), "+f"(d[O + 7]),
          "+f"(d[O + 8]), "+f"(d[O + 9]), "+f"(d[O + 10]), "+f"(d[O + 11]), "+f"(d[O + 12]), "+f"(d[O + 13]), "+f"(d[O + 14]), "+f"(d[O + 15]),
          "+f"(d[O + 16]), "+f"(d[O + 17]), "+f"(d[O + 18]), "+f"(d[O + 19]), "+f"(d[O + 20]), "+f"(d[O + 21]), "+f"(d[O + 22]), "+f"(d[O + 23]),
          "+f"(d[O + 24]), "+f"(d[O + 25]), "+f"(d[O + 26]), "+f"(d[O + 27]), "+f"(d[O + 28]), "+f"(d[O + 29]), "+f"(d[O + 30]), "+f"(d[O + 31])
        : "l"(da), "l"(db));
}


struct Idx {
    uint32_t lane, warp, w4, q4, g8, prow, pan;
    __device__ __forceinline__ Idx() {
        uint32_t t; asm volatile("mov.u32 %0, %%tid.x;" : "=r"(t));
        lane = t & 31; warp = t >> 5; w4 = warp & 3; q4 = lane & 3; g8 = lane >> 2;
        prow = w4 * 16 + ((lane >> 3) & 1) * 8 + (lane & 7);
        pan = prow * 128 + (((lane >> 4) ^ (lane & 7)) << 4);
    }
};
#define IDX() const Idx ix; const uint32_t lane = ix.lane, warp = ix.warp, w4 = ix.w4, q4 = ix.q4, g8 = ix.g8, prow = ix.prow, pan_addr = ix.pan; \
    (void)lane; (void)warp; (void)w4; (void)q4; (void)g8; (void)prow; (void)pan_addr;

struct Ring {
    uint32_t slot, par;
};
__device__ __forceinline__ uint32_t BAR_FULL(uint32_t sb, uint32_t s) { return sb + OFF_BAR + 8 * s; }
__device__ __forceinline__ uint32_t BAR_EMPTY(uint32_t sb, uint32_t s) { return sb + OFF_BAR + 48 + 8 * s; }
__device__ __forceinline__ uint32_t BAR_SFULL(uint32_t sb, uint32_t i) { return sb + OFF_BAR + 96 + 8 * i; }
__device__ __forceinline__ uint32_t BAR_ONE(uint32_t sb, uint32_t i) { return sb + OFF_BAR + 128 + 8 * i; }
enum { EV_X1, EV_WIN, EV_WINL = EV_WIN + 3, EV_X, EV_ST0, EV_GA, EV_GB, EV_P2, EV_LAG0, EV_LAG1, EV_LAG2, EV_LAG3, EV_LAG4, EV_LAG5, EV_HB, EV_H, EV_H1, EV_H2, EV_H3, EV_SENT, EV_SEC, EV_BACK, EV_BACK1, EV_A0, EV_A0L = EV_A0 + 3, EV_PAR, EV_COUNT };

static_assert(128 + 8 * EV_COUNT <= 384, "");

enum { K_ABS, K_OWN, K_PANEL };
enum { F_WRAP = 1, F_TWICE = 2, F_SKIP = 4, F_EARLY = 8, F_JOIN = 16 };
constexpr uint32_t pre_ev(uint32_t ev) { return 128 + 8 * ev; }
constexpr uint32_t pre_sfull(uint32_t i, uint32_t par) { return 96 + 8 * i + par; }
constexpr uint4 seg(uint32_t n, uint32_t kind, uint32_t a, uint32_t step, uint32_t q, uint32_t jump, uint32_t flags, uint32_t map, uint32_t kb, uint32_t pre = 0,
                    uint32_t blkj = 0, uint32_t blk = 0, uint32_t split = 0, uint32_t cnt = 0) {
    return uint4{n | (127 + q) / q << 8 | flags << 16 | map << 24, kind | a << 2 | step << 16 | jump / 64 << 24, kb | blkj << 8 | blk << 12 | split << 20, pre | cnt << 24};
}
constexpr int NSEG = 15;
__device__ const uint4 g_sched[4][NSEG] = {
    {seg(NSLOT, K_ABS, 0, 0, 1, 0, F_SKIP, L_WQKV, 0),
     seg(27 - 2 * NQ, K_PANEL, 1, 32, 2, 64, 0, L_WQKV, 24, 0, 2, 0, 1), seg(2 * NQ, K_PANEL, 28 - 2 * NQ, 32, 2, 64, 0, L_WKV, 16, 0, 2, 0, 1),
     seg(NQ, K_PANEL, 28 - 2 * NQ, 64, 1, 64, 0, L_WQ, 16, 0, 2, 0, 3), seg(NS, K_PANEL, 28 - 2 * NQ - 2 * NS, 64, 1, 64, 0, L_WQ1, 8, 0, 2, 1, 4),
     seg(2, K_OWN, 0, 64, 32, 0, 0, L_WO, 16, 0, 2, 0, 3), seg(14, K_PANEL, 0, 64, 1, 64, 0, L_WO, 16, 0, 2, 0, 3),
     seg(4, K_OWN, 0, 32, 32, 0, F_TWICE, L_WG, 24, 0, 7, 0, 2), seg(28, K_PANEL, 0, 32, 2, 64, F_WRAP, L_WG, 24, 0, 7, 0, 2),
     seg(32, K_ABS, 0, 32, 32, 0, 0, L_WG, 16, 0, 7, 3, 2), seg(32, K_ABS, 0, 32, 32, 0, 0, L_WG, 16, 0, 7, 5, 2),
     seg(16, K_ABS, 0, 64, 2, 320, 0, L_WD, 16, 0, 2, 0, 3), seg(16, K_ABS, 6, 64, 2, 320, 0, L_WD, 16, 0, 2, 0, 3), seg(16, K_ABS, 10, 64, 2, 320, 0, L_WD, 16, 0, 2, 0, 3),
     seg(8, K_ABS, 4, 64, 1, 384, 0, L_WD3, 16, 0, 2, 0, 3)},
    {seg(28, K_PANEL, 0, 32, 2, 64, F_EARLY, L_H1, 8, pre_sfull(2, 0), 0, 0, 0, 1),
     seg(NQ, K_PANEL, 28 - 2 * NQ, 64, 1, 64, 0, L_H1Q, 16), seg(NS, K_PANEL, 28 - 2 * NQ - 2 * NS, 64, 1, 64, 0, L_H1Q, 16),
     seg(2, K_OWN, 0, 64, 32, 0, 0, L_X, 16), seg(14, K_PANEL, 0, 64, 1, 64, 0, L_O, 16, pre_sfull(0, 1), 0, 0, 0, 2),
     seg(28, K_PANEL, 0, 32, 2, 64, F_EARLY, L_H2, 8, pre_sfull(2, 0), 0, 0, 0, 3),
     seg(32, K_ABS, 0, 32, 32, 0, 0, L_H2, 8, pre_ev(EV_SENT)), seg(32, K_ABS, 0, 32, 32, 0, 0, L_H2, 8),
     seg(16, K_ABS, 0, 64, 2, 320, 0, L_HB, 16, pre_ev(EV_H)), seg(16, K_ABS, 6, 64, 2, 320, 0, L_HB, 16, pre_ev(EV_H1)), seg(16, K_ABS, 10, 64, 2, 320, 0, L_HB, 16, pre_ev(EV_H2)),
     seg(8, K_ABS, 4, 64, 1, 384, 0, L_HB, 16, pre_ev(EV_H3))},
    {seg(64 % (2 * NSLOT), K_ABS, 0, 0, 1, 0, F_SKIP, L_WGX, 0),
     seg(16, K_ABS, 0, 32, 2, 64, 0, L_WGX, 16, pre_ev(EV_SEC), 0, 0, 2), seg(16, K_ABS, 2, 32, 2, 64, 0, L_WGX, 16, 0, 0, 0, 2),
     seg(32, K_ABS, 0, 32, 32, 0, 0, L_WGX, 16, 0, 0, 0, 2), seg(32, K_ABS, 0, 32, 32, 0, 0, L_WGX, 16, 0, 0, 0, 2), seg(32, K_ABS, 0, 32, 32, 0, 0, L_WGX, 16, 0, 0, 0, 2)},
    {seg(16, K_ABS, 0, 64, 32, 0, F_TWICE, L_WMOD, 32, 0, 4, 32), seg(16, K_ABS, 0, 64, 32, 0, F_TWICE, L_WMOD, 32, 0, 4, 48),
     seg(16, K_ABS, 0, 64, 32, 0, F_TWICE, L_WMOD, 32, 0, 4, 64), seg(16, K_ABS, 0, 64, 32, 0, F_TWICE, L_WMOD, 32, 0, 4, 80),
     seg(16, K_ABS, 0, 32, 2, 64, F_JOIN, L_H2, 8, 0, 0, 0, 0, 3), seg(16, K_ABS, 2, 32, 2, 64, 0, L_H2, 8, 0, 0, 0, 0, 3),
     seg(32, K_ABS, 0, 32, 32, 0, 0, L_H2, 8, 0, 0, 2, 0, 3), seg(32, K_ABS, 0, 32, 32, 0, 0, L_H2, 8, 0, 0, 4, 0, 3), seg(32, K_ABS, 0, 32, 32, 0, 0, L_H2, 8, 0, 0, 6, 0, 3)}};

struct Pipe {
    uint32_t sb, slot, par, tok, rel;
    __device__ __forceinline__ void arm() {
        uint32_t t, a; asm volatile("mov.u32 %0, %%tid.x;" : "=r"(t));
        asm("mapa.shared::cluster.u32 %0, %1, %2;" : "=r"(a) : "r"(BAR_EMPTY(sb, 0)), "r"((t >> 5) & 1));
        tok = __shfl_sync(0xffffffffu, (t & 95u) == 0 ? a : 0, t & 31);
    }
    __device__ __forceinline__ uint32_t stage() {
        mbar_wait(BAR_FULL(sb, slot), par);
        return d16(sb) + slot * (SLOT >> 4);
    }
    __device__ __forceinline__ void release() { if (rel) asm volatile("mbarrier.arrive.shared::cluster.b64 _, [%0];" :: "r"(rel) : "memory"); rel = 0; }
    __device__ __forceinline__ void issued() {
        wg_commit(); wg_wait<1>(); release();
        if (tok) rel = tok + 8 * slot;
        if (++slot == NSLOT) { slot = 0; par ^= 1; }
    }
    __device__ __forceinline__ void drain() { wg_wait<0>(); release(); }
    __device__ __forceinline__ void at(int stage) { slot = stage % NSLOT; par = (stage / NSLOT) & 1; }
};
template <int L> __device__ __forceinline__ void fresh(float (&a)[L]) {
#pragma unroll
    for (int i = 0; i < L; ++i) asm volatile("" : "=f"(a[i]));
}
enum { M_QKV, M_Q0KV, M_KV, M_GU3, M_GU2 };
template <int MODE, bool OWN = false, int L1, int L2>
__device__ __forceinline__ void step32(float (&a1)[L1], float (&a2)[L2], Pipe& p, uint32_t wg, uint32_t add = 1, uint32_t own = 0) {
    constexpr uint32_t KS = MODE < M_KV ? 12288 : MODE == M_KV ? 8192 : 2048, LBO = MODE <= M_KV ? 2048 : 4096;
    const uint32_t st = p.stage();
    wg_fence();
#pragma unroll
    for (int k = 0; k < 2; ++k) {
        const uint64_t da = OWN ? mk_desc(own, k * 32, 16, 1024, 1) : mk_desc(st + wg * 256, k * 32, 16, 512, 2);
        const uint64_t d0 = mk_desc(st, 8192 + (MODE < M_KV ? 4096 : 0) + k * KS, LBO, 1024, 1), d1 = mk_desc(st, 8192 + (MODE < M_KV ? 0 : 12288) + k * KS, LBO, 1024, 1);
        if constexpr (MODE == M_GU3) { wgmma_n176(a1, da, d0, k ? 1 : add); wgmma_n176(a2, da, d1, k ? 1 : add); }
        else wgmma_n256(a1, da, d0, k ? 1 : add);
        if constexpr (MODE == M_QKV) wgmma_n128(a2, da, d1, k ? 1 : add);
        if constexpr (MODE == M_Q0KV) wgmma_n64<0>(a2, da, d1);
    }
    p.issued();
}
struct Nop { __device__ __forceinline__ void operator()() const {} };
template <class F = Nop>
__device__ __forceinline__ void step64(float (&acc)[64], Pipe& p, uint32_t wg, uint32_t add = 1, int own = -1, F landed = F()) {
    const uint32_t st = p.stage();
    landed();
    const uint32_t sa = own >= 0 ? d16(p.sb) + OFF_STG / 16 + wg * 512 + own * 1024 : st + wg * 512;
    wg_fence();
#pragma unroll
    for (int k = 0; k < 4; ++k) {
        const uint64_t da = mk_desc(sa, k * 32, 16, 1024, 1), db = mk_desc(st, 16384 + k * 2048, 8192, 1024, 1);
        wgmma_n128(acc, da, db, k ? 1 : add);
    }
    p.issued();
}
__device__ __forceinline__ void run64_landed(float (&acc)[64], Pipe& p, uint32_t wg, int n) {
#pragma unroll 1
    while (true) {
        const uint32_t st = d16(p.sb) + p.slot * (SLOT >> 4);
        wg_fence();
#pragma unroll
        for (int k = 0; k < 4; ++k) wgmma_n128(acc, mk_desc(st + wg * 512, k * 32, 16, 1024, 1), mk_desc(st, 16384 + k * 2048, 8192, 1024, 1));
        p.issued();
        if (--n == 0) break;
        p.stage();
    }
}
__device__ __forceinline__ void rename(float (&d)[64], const float (&a)[64]) {
#pragma unroll
    for (int i = 0; i < 64; ++i) asm volatile("mov.b32 %0, %1;" : "=f"(d[i]) : "f"(a[i]));
}
template <int MODE, int ST, int MORE, int L1, int L2>
__device__ __forceinline__ void run_own(float (&a256)[L1], float (&a128)[L2], Pipe& p, uint32_t wg) {
    const uint32_t a0 = d16(p.sb) + OFF_OWN / 16 + wg * 512;
    p.at(ST);
    fresh(a256); fresh(a128);
#pragma unroll 1
    for (int i = 0; i < 4; ++i) step32<MODE, true>(a256, a128, p, wg, i, a0 + (i >> 1) * 1024 + (i & 1) * 4);
    p.drain();
    mbar_arrive_if0(BAR_FULL(p.sb, 5), threadIdx.x & 127);
#pragma unroll 1
    for (int i = 0; i < 4 + MORE; ++i) {
        if (i < 2) p.at(i ? ST + 6 : ST + 4);
        if (wg == 0 && i < 4) mbar_wait(BAR_ONE(p.sb, EV_A0 + i), ST > 0);
        step32<MODE>(a256, a128, p, wg);
    }
    p.at(ST + 9 + MORE);
}
template <int LG, class Step>
__device__ __forceinline__ void run(int n, uint32_t wg, uint32_t ev, Step step) {
    const int last = LG ? (wg ? EARLY : LG) : 0;
#pragma unroll 1
    for (int part = 0; ; ++part) {
#pragma unroll 1
        for (int i = part ? last : n - last; i > 0; --i) step();
        if (part || !LG) break;
        mbar_arrive_if0(ev, threadIdx.x ^ 128);
        if (wg == 0) mbar_wait(ev, 0);
    }
}

struct LnRow { float rs0, nm0, rs1, nm1; };
__device__ __forceinline__ void publish_stats(uint4* dst, float s0, float q0, float s1, float q1, uint32_t tag) {
    st_pkt16(dst, (__float_as_uint(s0) & ~3u) | tag, __float_as_uint(s1), __float_as_uint(q0), __float_as_uint(q1));
}
template <class F = Nop>
__device__ __forceinline__ LnRow merge_stats(const uint4* src, uint32_t tag, F meanwhile = F()) {
    uint4 a = ld_pkt16(src), b = ld_pkt16(src + S_ / 2);
    meanwhile();
    while (!__all_sync(0xffffffffu, (a.x & b.x & tag) != 0)) { a = ld_pkt16(src); b = ld_pkt16(src + S_ / 2); }
    float v[4] = {__uint_as_float(a.x) + __uint_as_float(b.x), __uint_as_float(a.y) + __uint_as_float(b.y),
                  __uint_as_float(a.z) + __uint_as_float(b.z), __uint_as_float(a.w) + __uint_as_float(b.w)};
#pragma unroll
    for (int o = 1; o < 4; o <<= 1)
#pragma unroll
        for (int i = 0; i < 4; ++i) v[i] += __shfl_xor_sync(0xffffffffu, v[i], o);
    const float m0 = v[0] * (1.f / D_), m1 = v[1] * (1.f / D_);
    const float r0 = rsq(fmaxf(fmaf(-m0, m0, v[2] * (1.f / D_)), 0.f) + 1e-5f), r1 = rsq(fmaxf(fmaf(-m1, m1, v[3] * (1.f / D_)), 0.f) + 1e-5f);
    return LnRow{r0, -m0 * r0, r1, -m1 * r1};
}
__device__ __forceinline__ void ln_norm(uint32_t (&y)[32], const float (&x)[64], const LnRow& n) {
#pragma unroll
    for (int e = 0; e < 32; ++e) {
        const float rs = (e & 1) ? n.rs1 : n.rs0, nm = (e & 1) ? n.nm1 : n.nm0;
        y[e] = pack2(fmaf(x[2 * e], rs, nm), fmaf(x[2 * e + 1], rs, nm));
    }
}
__device__ __forceinline__ void ln_emit(const uint32_t (&y)[32], const uint4 (&p)[8], uint32_t sb, uint32_t wg, const Idx& ix) {
#pragma unroll
    for (int i = 0; i < 8; ++i) {
        uint32_t r[4];
#pragma unroll
        for (int e = 0; e < 4; ++e) r[e] = hfma2_bf16(y[4 * i + e], e < 2 ? p[i].z : p[i].w, e < 2 ? p[i].x : p[i].y);
        stsm4(sb + OFF_OWN + wg * 8192 + (i >> 2) * 16384 + (ix.pan ^ ((i & 3) << 5)), r[0], r[1], r[2], r[3]);
        if (i == 3) { __syncwarp(); if (ix.lane == 0) mbar_arrive(BAR_SFULL(sb, wg * 2)); }
    }
    fence_async_smem();
    __syncwarp();
    if (ix.lane == 0) mbar_arrive(BAR_SFULL(sb, wg * 2 + 1));
    bar_sync(1 + wg, 128);
}
template <int P>
__device__ __forceinline__ void load_panel(uint32_t (&r)[32], uint32_t p) {
    IDX();
#pragma unroll
    for (int i = 4 * P; i < 4 * P + 4; ++i) ldsm4(p + (pan_addr ^ ((i & 3) << 5)), r[4 * i], r[4 * i + 1], r[4 * i + 2], r[4 * i + 3]);
}
template <int E0 = 0, int E1 = 32>
__device__ __forceinline__ void widen(float (&x)[64], const uint32_t (&r)[32]) {
#pragma unroll
    for (int e = E0; e < E1; ++e) asm volatile("shl.b32 %0, %2, 16;\nand.b32 %1, %2, 0xFFFF0000;" : "=&f"(x[2 * e]), "=f"(x[2 * e + 1]) : "r"(r[e]));
}
template <int I0 = 0, int I1 = 8>
__device__ __forceinline__ void load_table(uint4 (&t)[8], uint32_t tab) {
#pragma unroll
    for (int i = I0; i < I1; ++i) t[i] = lds128(tab + i * 64 + (threadIdx.x & 3) * 16);
}
template <int STRIDE, int P0, int P1, class Step>
__device__ __forceinline__ void epilogue_operands(float (&x)[64], uint4 (&g)[8], uint32_t (&r)[32], uint32_t src, uint32_t tab, Step step) {
    fresh(x);
#pragma unroll
    for (int i = 0; i < (P1 > 6 ? 8 : 0); ++i) asm volatile("" : "=r"(g[i].x), "=r"(g[i].y), "=r"(g[i].z), "=r"(g[i].w));
#pragma unroll 1
    for (int it = P0 * STRIDE; it < P1 * STRIDE; ++it) {
        step([&] {
            if (it == 0) load_panel<0>(r, src);
            if (it == STRIDE) load_panel<1>(r, src + 16384);
            if (it == 6 * STRIDE) load_table<0, 4>(g, tab);
            if (it == 7 * STRIDE) load_table<4, 8>(g, tab);
        });
        if (it == 2 * STRIDE) widen<0, 8>(x, r);
        if (it == 3 * STRIDE) widen<8, 16>(x, r);
        if (it == 4 * STRIDE) widen<16, 24>(x, r);
        if (it == 5 * STRIDE) widen<24, 32>(x, r);
    }
}
__device__ __forceinline__ float gate_of(const uint4 (&t)[8], int e) {
    const uint4 v = t[e >> 3];
    return __uint_as_float((e & 4) ? ((e & 1) ? v.w : v.z) : ((e & 1) ? v.y : v.x));
}
__device__ __forceinline__ constexpr int glu_at(int i, int e) { return (i >> 2) * 64 + ((i >> 1) & 1) * 16 + (e >> 1) * 4 + (i & 1) * 2 + (e & 1); }
struct Packed {
    const uint32_t (&a)[64];
    __device__ __forceinline__ float operator()(int e) const {
        float v;
        if (e & 1) asm volatile("and.b32 %0, %1, 0xFFFF0000;" : "=f"(v) : "r"(a[e >> 1])); else asm volatile("shl.b32 %0, %1, 16;" : "=f"(v) : "r"(a[e >> 1]));
        return v;
    }
};
__device__ __forceinline__ uint32_t glu2(float g0, float g1, float u0, float u1) {
    float t0, t1;
    asm volatile("tanh.approx.f32 %0, %1;" : "=f"(t0) : "f"(g0));
    asm volatile("tanh.approx.f32 %0, %1;" : "=f"(t1) : "f"(g1));
    return pack2(fmaf(t0, u0, u0), fmaf(t1, u1, u1));
}
template <int N, int STEP, int OG, int OU, int L>
__device__ __forceinline__ void glu_now(const float (&g)[L], const float (&u)[L], __nv_bfloat16* dst) {
#pragma unroll
    for (int i = 0; i < 2 * N; ++i) {
        const int e = (i >> 1) * 8 + (i & 1) * 2;
        asm volatile("st.global.v2.u32 [%0], {%1, %2};" :: "l"(dst + (i & 1) * 8 * F_ + (i >> 1) * STEP),
            "r"(glu2(g[OG + e], g[OG + e + 1], u[OU + e], u[OU + e + 1])), "r"(glu2(g[OG + e + 4], g[OG + e + 5], u[OU + e + 4], u[OU + e + 5])) : "memory");
    }
}
template <class Step>
__device__ __forceinline__ void glu_under(uint32_t (&a)[64], __nv_bfloat16* dst, int n, Step step) {
#pragma unroll 1
    for (int it = -n; it < 16; ++it) {
        step();
        if (it >= 0 && !(it & 1)) {
#pragma unroll
            for (int i = 0; i < 4; ++i)
                if ((it & 7) == 2 * i) {
                    const Packed v{a};
                    uint32_t r[4];
#pragma unroll
                    for (int c = 0; c < 4; ++c) { const int e = glu_at(i, 2 * c); r[c] = glu2(v(e), v(e + 1), v(32 + e), v(33 + e)); }
                    asm volatile("st.global.v4.u32 [%0], {%1, %2, %3, %4};" :: "l"(dst + (i & 1) * 8 * F_ + (i >> 1) * 32), "r"(r[0]), "r"(r[1]), "r"(r[2]), "r"(r[3]) : "memory");
#pragma unroll
                    for (int c = 0; c < 8; ++c) { const int e = (glu_at(i, (2 * c) & 7) >> 1) + (c >> 2) * 16; a[e] = a[32 + e]; }
                    if (i == 3) dst += 64;
                }
        }
    }
}
__device__ __forceinline__ void pack_all(uint32_t (&d)[64], const float (&a)[128]) {
#pragma unroll
    for (int i = 0; i < 64; ++i) d[i] = pack2(a[2 * i], a[2 * i + 1]);
}

__global__ void __launch_bounds__(384, 1)
fused_block_kernel(const __grid_constant__ Ptrs pt, const __grid_constant__ Maps mp) {
    uint32_t* const g_flags = pt.mail->flags;
    uint2* const g_mod = pt.mail->mod;
    uint4* const g_st1 = pt.mail->st1;
    uint32_t* const g_par2 = pt.mail->par2;
    uint4* const g_halo = pt.mail->halo;
    const __nv_bfloat16* __restrict__ cvec = pt.c;
    asm volatile("{\n.reg .pred p;\nsetp.eq.u32 p, %1, 1;\n@p prefetch.global.L2 [%0];\n}"
        :: "l"(pt.x + ((blockIdx.x & 127) * 16 + ((threadIdx.x >> 4) & 7) * 2 + 1) * D_ + (threadIdx.x & 15) * 64), "r"(threadIdx.x >> 7));
    if (threadIdx.x == 0) { prefetch_map(&mp.x); prefetch_map(&mp.wm); }
    uint32_t ep = 0;
#define LOAD_EP() asm volatile("ld.relaxed.gpu.global.u32 %0, [%1];" : "=r"(ep) : "l"(&g_flags[FL_DONE + (threadIdx.x & blockIdx.y)]) : "memory")
    if (threadIdx.x >= 256) LOAD_EP();
    extern __shared__ __align__(1024) uint8_t smem[];
    const uint32_t sb = smem_u32(smem) + 1024;
    const uint32_t tid = threadIdx.x, tw = tid & 127, lane = tid & 31;
    const uint32_t warp = __shfl_sync(0xffffffffu, tid >> 5, 0), wg = warp >> 2;
    uint32_t rank; asm("mov.u32 %0, %%cluster_ctarank;" : "=r"(rank));
    rank = __shfl_sync(0xffffffffu, rank, 0);
    uint32_t smid; asm volatile("mov.u32 %0, %%smid;" : "=r"(smid));
    const int c = __shfl_sync(0xffffffffu, smid >> 1, 0);
    const int q7 = ((c - 32) * 37) >> 8;
    const bool aux = (c >> 1) == 30;
    const int grp = c < 32 ? c & 7 : c < 60 ? c - 31 - 7 * q7 : c == 61 ? 4 : 0;
    const int jhi = aux ? (c - 60) * 2 + rank : c - 58, jlo = c < 32 ? c >> 3 : 4 + q7, j = c < 60 ? jlo : jhi;
    const int m = grp * 2 + rank;
    const int cid = (c < 60 ? c : c - 2) * 2 + rank;
    if (warp == 1 && !aux && elect_one()) {
        mbar_init(BAR_ONE(sb, EV_X1), 1);
        mbar_expect_tx(BAR_ONE(sb, EV_X1), 16384);
#pragma unroll
        for (int i = 0; i < 2; ++i) tma_load(sb + OFF_STG + i * 16384 + 8192, &mp.x, D_ + j * 128 + i * 64, m * 64, BAR_ONE(sb, EV_X1));
#pragma unroll
        for (int i = 0; i < 4; ++i) mbar_init(BAR_ONE(sb, EV_WIN + i), 1);
#pragma unroll
        for (int i = 0; i < 4; ++i) {
            mbar_expect_tx(BAR_ONE(sb, EV_WIN + i), 8192);
            tma_load(sb + OFF_OWN + i * 8192, &mp.wm, (cid >> 2) * 64, (cid & 3) * 256 + i * 64, BAR_ONE(sb, EV_WIN + i));
        }
        asm volatile("fence.mbarrier_init.release.cluster;" ::: "memory");
    }
    __syncwarp();

    bool cluster_arrive_early = false;
    if (wg < 2) {
      cluster_arrive();
      if (aux) {
        LOAD_EP();
        cluster_wait();
        ep = __shfl_sync(0xffffffffu, ep, 0) / NCTA + 1;
        Pipe pp{sb, 0, 0, 0, 0};
        pp.arm();
#pragma unroll 1
        for (int p = 0; p < 4; ++p) {
            float acc[64];
            fresh(acc);
            pp.at(16 * p);
#pragma unroll 1
            for (int kc = 0; kc < 16; ++kc) {
                const uint32_t st = pp.stage();
                wg_fence();
#pragma unroll
                for (int k = 0; k < 4; ++k) wgmma_n128(acc, mk_desc(d16(sb) + kc * 64, OFF_STG + k * 32, 16, 0, 1), mk_desc(st + wg * 1024, k * 2048, 8192, 1024, 1), k ? 1 : kc);
                pp.issued();
            }
            pp.drain();
            if (tw < 32) {
                if (tw < 4) {
#pragma unroll
                    for (int jn = 0; jn < 16; ++jn) sts32(sb + OFF_TAB + wg * 256 + (jn * 4 + tw) * 4, pack2(acc[jn * 4], acc[jn * 4 + 1]));
                }
                __syncwarp();
#pragma unroll 1
                for (uint32_t t = wg * 64 + tw; t < wg * 64 + 64; t += 32) {
                    const uint32_t val = lds32(sb + OFF_TAB + t * 4);
                    const float one = p == 2 ? 1.f : 0.f;
                    if (p == 0 || p == 3) st_pkt(g_mod + (8 + p * 4 + j) * 128 + t, val, ep);
                    else g_par2[(j * 16 + (t >> 3)) * 16 + (t & 3) * 4 + (p - 1) * 2 + ((t >> 2) & 1)] = pack2(0.5f * bf_round(one + bf_lo(val)), 0.5f * bf_round(one + bf_hi(val)));
                }
                __syncwarp();
                if (tw == 0 && p == 2) asm volatile("red.release.gpu.global.add.u32 [%0], 1;" :: "l"(&g_flags[FL_LN2]) : "memory");
            }
        }
#pragma unroll 1
        for (int p = 0; p < 4; ++p) {
            float acc[128], none[8];
            pp.at(64 + 32 * p);
            fresh(acc);
            uint32_t add = 0;
            run<LAGX>(32, wg, BAR_ONE(sb, EV_LAG0 + p), [&] { step32<M_GU2>(acc, none, pp, wg, add); add = 1; });
            pp.drain();
            __nv_bfloat16* const dst = pt.hb + ((m + 2 * p) * 128 + warp * 16 + (lane >> 2)) * F_ + 176 + (lane & 3) * 4;
            glu_now<4, 448, 0, 32>(acc, acc, dst);
            glu_now<4, 448, 64, 96>(acc, acc, dst + 4 * 448);
            __syncwarp();
            mbar_arrive_if0(BAR_ONE(sb, EV_HB), lane);
        }
      } else {
        Pipe pp{sb, 0, 0, 0, 0};
        pp.arm();
        {
            IDX();
            uint4* const st1 = g_st1 + m * 64 + warp * 8 + g8;
            if (q4 == (g8 >> 1)) st_pkt16(st1 + j * (S_ / 2), 0, 0, 0, 0);
            cluster_wait();
            uint32_t xr[32];
            mbar_wait(BAR_ONE(sb, wg ? EV_X1 : EV_X), 0);
            float sm[4] = {0.f, 0.f, 0.f, 0.f}, g0[4] = {0.f, 0.f, 0.f, 0.f}, g1[4] = {0.f, 0.f, 0.f, 0.f};
#pragma unroll
            for (int i = 0; i < 8; ++i) {
                ldsm4(sb + OFF_STG + wg * 8192 + (i >> 2) * 16384 + (pan_addr ^ ((i & 3) << 5)), xr[4 * i], xr[4 * i + 1], xr[4 * i + 2], xr[4 * i + 3]);
                mma16816(sm, xr[4 * i], xr[4 * i + 1], xr[4 * i + 2], xr[4 * i + 3], 0x3F803F80u, 0x3F803F80u);
                mma16816(g0, xr[4 * i], xr[4 * i + 1], xr[4 * i + 2], xr[4 * i + 3], xr[4 * i], xr[4 * i + 2]);
                mma16816(g1, xr[4 * i], xr[4 * i + 1], xr[4 * i + 2], xr[4 * i + 3], xr[4 * i + 1], xr[4 * i + 3]);
            }
            if (q4 == (g8 >> 1))
                publish_stats(st1 + j * (S_ / 2), sm[0], (g8 & 1) ? g0[1] : g0[0], sm[2], (g8 & 1) ? g1[3] : g1[2], 1);
            float xf[64];
            widen(xf, xr);
            mbar_wait(BAR_ONE(sb, EV_WINL), 0);
            const LnRow n1 = merge_stats(st1 + q4 * S_, 1);
            mbar_arrive_if0(BAR_ONE(sb, EV_ST0), tid & 159);
            ln_norm(xr, xf, n1);
            asm volatile("setmaxnreg.inc.sync.aligned.u32 %0;" :: "n"(RC));
            mbar_wait(BAR_ONE(sb, EV_PAR), 0);
            uint4 par[8];
            load_table(par, sb + OFF_PAR);
            ln_emit(xr, par, sb, wg, ix);
        }
        uint32_t xr[32];
        {
            float qa[64];
            uint32_t kl[16], kh[16], kp[16];
            uint32_t v0[32], v1[32];
            {
                float kv[128];
                float q1[64], q2[64];
                run_own<M_QKV, 0, 24 - 2 * NS - 2 * NQ>(kv, q1, pp, wg);
                pp.drain();
                rename(q2, q1);
                run<0>(2 * NS, wg, 0, [&] { step32<M_Q0KV>(kv, q2, pp, wg); });
                pp.drain();
                rename(qa, q2);
                run<LAGQ>(2 * NQ, wg, BAR_ONE(sb, EV_LAG0), [&] { step32<M_KV>(kv, qa, pp, wg); });
                pp.stage();
                pp.drain();
                IDX();
#pragma unroll
                for (int t = 0; t < 16; ++t) v1[(t >> 1) * 4 + 2 + (t & 1)] = movm(pack2(kv[66 + 4 * t], kv[67 + 4 * t]));
#pragma unroll
                for (int t = 0; t < 16; ++t) {
                    kl[t] = pack2(kv[4 * t], kv[4 * t + 1]); kh[t] = pack2(kv[4 * t + 2], kv[4 * t + 3]);
                    v1[(t >> 1) * 4 + (t & 1)] = pack2(kv[64 + 4 * t], kv[65 + 4 * t]);
                }
                if (w4 < 3) {
                    const uint32_t dst = sb + OFF_STG + wg * 8192 + (w4 >> 1) * 16384 + (w4 & 1) * 4096;
#pragma unroll
                    for (int i = 0; i < 4; ++i) sts128(dst + i * 512 + lane * 16, kh[4 * i], kh[4 * i + 1], kh[4 * i + 2], kh[4 * i + 3]);
#pragma unroll
                    for (int i = 0; i < 8; ++i) sts64(dst + 2048 + i * 256 + lane * 8, v1[4 * i + 2], v1[4 * i + 3]);
                } else if (m < 15) {
                    uint4* const dst = g_halo + (m * 8 + j) * 512 + wg * 256;
#pragma unroll
                    for (int i = 0; i < 4; ++i) { if (!kh[4 * i]) kh[4 * i] = 0x8000u; st_pkt16(dst + i * 32 + lane, kh[4 * i], kh[4 * i + 1], kh[4 * i + 2], kh[4 * i + 3]); }
#pragma unroll
                    for (int i = 0; i < 8; ++i) { if (!v1[4 * i + 2]) v1[4 * i + 2] = 0x8000u; st_pkt((uint2*)(dst + 128) + i * 32 + lane, v1[4 * i + 2], v1[4 * i + 3]); }
                }
            }
            pp.at(ST_Q);
            run64_landed(qa, pp, wg, QA);
            pp.stage();
            IDX();
            const uint4* const halo = g_halo + ((m - 1) * 8 + j) * 512 + wg * 256;
            auto fetch_halo = [&] {
#pragma unroll
                for (int i = 0; i < 4; ++i) {
                    const uint4 t = ld_pkt16(halo + i * 32 + lane);
                    kp[4 * i] = t.x; kp[4 * i + 1] = t.y; kp[4 * i + 2] = t.z; kp[4 * i + 3] = t.w;
                }
#pragma unroll
                for (int i = 0; i < 8; ++i) {
                    const uint2 t = ld_pkt((const uint2*)(halo + 128) + i * 32 + lane);
                    v0[4 * i] = t.x; v0[4 * i + 1] = t.y;
                }
            };
            bar_sync(1 + wg, 128);
#pragma unroll
            for (int t = 0; t < 16; ++t) v1[(t >> 1) * 4 + (t & 1)] = movm(v1[(t >> 1) * 4 + (t & 1)]);
            if (w4 == 0 && m > 0) fetch_halo();
            else {
                const uint32_t from = w4 ? w4 - 1 : 0, src = sb + OFF_STG + wg * 8192 + (from >> 1) * 16384 + (from & 1) * 4096;
#pragma unroll
                for (int i = 0; i < 4; ++i) { const uint4 t = lds128(src + i * 512 + lane * 16); kp[4 * i] = t.x; kp[4 * i + 1] = t.y; kp[4 * i + 2] = t.z; kp[4 * i + 3] = t.w; }
#pragma unroll
                for (int i = 0; i < 8; ++i) { const uint2 t = lds64(src + 2048 + i * 256 + lane * 8); v0[4 * i] = t.x; v0[4 * i + 1] = t.y; }
            }
            pp.at(ST_Q + QA);
            run64_landed(qa, pp, wg, NQ - QA);
#pragma unroll
            for (int t = 0; t < 16; ++t) asm volatile("mov.b32 %0, %1;" : "=r"(v0[(t >> 1) * 4 + 2 + (t & 1)]) : "r"(v1[(t >> 1) * 4 + (t & 1)]));
            bar_sync(1 + wg, 128);
            if (w4 == 0 && m > 0) {
                while (true) {
                    bool ok = true;
#pragma unroll
                    for (int i = 0; i < 8; ++i) ok = ok && v0[4 * i] != 0 && kp[4 * (i & 3)] != 0;
                    if (__all_sync(0xffffffffu, ok)) break;
                    fetch_halo();
                }
            }
            pp.drain();
            float qb[64];
            rename(qb, qa);
            const bool lo0 = q4 * 2 > g8, lo1 = q4 * 2 + 1 > g8;
            const bool nopast = m == 0 && w4 == 0;
            const uint32_t lomask = (lo0 ? 0xFFFFu : 0u) | (lo1 ? 0xFFFF0000u : 0u);
            const float sl2 = 0.17677669529663687f * 1.4426950408889634f;
            const uint32_t oa = wg * 8192 + (w4 * 16 + (lane & 7)) * 128 + (((lane >> 3) ^ (lane & 7)) << 4);
#pragma unroll
            for (int hp = 0; hp < 2; ++hp) {
                if (hp) {
                    bar_sync(3, 256);
#pragma unroll 1
                    for (int it = 0; it < NS; ++it) {
                        pp.slot = (SWEEP >> (4 * it)) & 7; pp.par = (SWEEP >> (4 * it + 3)) & 1;
                        const uint32_t st = pp.stage();
                        wg_fence();
#pragma unroll
                        for (int k = 0; k < 4; ++k) wgmma_n64<32>(qb, mk_desc(st + wg * 512, k * 32, 16, 1024, 1), mk_desc(st, 16384 + k * 2048, 8192, 1024, 1));
                        pp.issued();
                        if (it == 0) pp.rel = 0;
                        if (it == SWO && pp.tok) asm volatile("mbarrier.arrive.shared::cluster.b64 _, [%0];" :: "r"(pp.tok + 8 * (SWEEP & 7)) : "memory");
                    }
                    mbar_wait(BAR_FULL(sb, ST_WO % NSLOT), (ST_WO / NSLOT) & 1);
                    pp.drain();
                    load_panel<0>(xr, sb + ST_WO % NSLOT * SLOT + wg * 8192);
                }
                float e0[4], e1[4], mx[4], sum[4];
#pragma unroll
                for (int hh = 0; hh < 2; ++hh) {
                    const int h = 2 * hp + hh;
                    uint32_t qf[8];
                    float s[3][4];
#pragma unroll
                    for (int i = 0; i < 8; ++i) qf[i] = pack2(qb[16 * h + 2 * i], qb[16 * h + 2 * i + 1]);
#pragma unroll
                    for (int nt = 0; nt < 3; ++nt) {
                        const uint32_t (&kk)[16] = nt == 0 ? kp : nt == 1 ? kl : kh;
                        s[nt][0] = s[nt][1] = s[nt][2] = s[nt][3] = 0.f;
                        mma16816(s[nt], qf[0], qf[1], qf[2], qf[3], kk[4 * h], kk[4 * h + 1]);
                        mma16816(s[nt], qf[4], qf[5], qf[6], qf[7], kk[4 * h + 2], kk[4 * h + 3]);
                    }
#pragma unroll
                    for (int hf = 0; hf < 2; ++hf) {
                        e0[2 * hh + hf] = lo0 ? ((hf == 0 && nopast) ? -INFINITY : s[hf][hf * 2]) : s[hf + 1][hf * 2];
                        e1[2 * hh + hf] = lo1 ? ((hf == 0 && nopast) ? -INFINITY : s[hf][hf * 2 + 1]) : s[hf + 1][hf * 2 + 1];
                        mx[2 * hh + hf] = fmaxf(e0[2 * hh + hf], e1[2 * hh + hf]);
                    }
                }
#pragma unroll
                for (int o = 1; o < 4; o <<= 1)
#pragma unroll
                    for (int u = 0; u < 4; ++u) mx[u] = fmaxf(mx[u], __shfl_xor_sync(0xffffffffu, mx[u], o));
#pragma unroll
                for (int u = 0; u < 4; ++u) {
                    const float c = -mx[u] * sl2;
                    e0[u] = ex2(fmaf(e0[u], sl2, c)); e1[u] = ex2(fmaf(e1[u], sl2, c));
                    sum[u] = e0[u] + e1[u];
                }
#pragma unroll
                for (int o = 1; o < 4; o <<= 1)
#pragma unroll
                    for (int u = 0; u < 4; ++u) sum[u] += __shfl_xor_sync(0xffffffffu, sum[u], o);
#pragma unroll
                for (int u = 0; u < 4; ++u) {
                    const int h = 2 * hp + (u >> 1), hf = u & 1;
                    const uint32_t (&vv)[32] = hf ? v1 : v0;
                    const float iv = rcp(sum[u]);
                    const uint32_t pr = pack2(e0[u] * iv, e1[u] * iv);
                    float o[2][4];
#pragma unroll
                    for (int t = 0; t < 2; ++t) {
                        o[t][0] = o[t][1] = o[t][2] = o[t][3] = 0.f;
                        mma16816(o[t], vv[8 * h + 4 * t], vv[8 * h + 4 * t + 1], vv[8 * h + 4 * t + 2], vv[8 * h + 4 * t + 3], pr & lomask, pr & ~lomask);
                    }
                    stsm4t(sb + OFF_STG + hp * 16384 + (oa ^ ((h & 1) << 6)) + hf * 1024, pack2(o[0][0], o[0][1]), pack2(o[0][2], o[0][3]), pack2(o[1][0], o[1][1]), pack2(o[1][2], o[1][3]));
                }
                __syncwarp();
                if (lane == 0) mbar_arrive(BAR_SFULL(sb, wg * 2 + hp));
            }
        }
        {
            float acc[64], xf[64];
            uint4 gt[8], par[8];
            fence_async_smem();
            bar_sync(3, 256);
            pp.at(ST_WO);
            mbar_wait(BAR_FULL(sb, (ST_WO + 1) % NSLOT), ((ST_WO + 1) / NSLOT) & 1);
            fresh(acc);
            step64(acc, pp, wg, 0, 0, [&] { load_panel<1>(xr, sb + (ST_WO + 1) % NSLOT * SLOT + wg * 8192); });
            step64(acc, pp, wg, 1, 1);
            fence_async_smem();
            bar_sync(1 + wg, 128);
            mbar_wait(BAR_ONE(sb, EV_GA), 0);
            load_table(gt, sb + OFF_TAB);
            pp.drain();
            uint4* const pub = g_st1 + __shfl_sync(0xffffffffu, j * (S_ / 2) + m * 64 + (tid >> 2), lane);
            pp.at(ST_WO + 2);
            epilogue_operands<1, 2, 6>(xf, gt, xr, 0, sb + OFF_TAB, [&](auto f) { step64(acc, pp, wg, 1, -1, f); });
            run<LAGW>(10, wg, BAR_ONE(sb, EV_LAG4), [&] { step64(acc, pp, wg); });
            pp.drain();
            float su[4] = {0.f, 0.f, 0.f, 0.f}, sq[4] = {0.f, 0.f, 0.f, 0.f};
#pragma unroll
            for (int e = 0; e < 64; ++e) {
                xf[e] = fmaf(gate_of(gt, e), acc[e], xf[e]);
                su[e & 3] += xf[e]; sq[e & 3] = fmaf(xf[e], xf[e], sq[e & 3]);
            }
            {
                float v[4] = {su[0] + su[1], sq[0] + sq[1], su[2] + su[3], sq[2] + sq[3]};
#pragma unroll
                for (int o = 1; o < 4; o <<= 1)
#pragma unroll
                    for (int i = 0; i < 4; ++i) v[i] += __shfl_xor_sync(0xffffffffu, v[i], o);
                if ((tid & 3) == 0) publish_stats(pub, v[0], v[1], v[2], v[3], 2);
            }
            IDX();
            mbar_wait(BAR_ONE(sb, EV_P2), 0);
#pragma unroll
            for (int i = 0; i < 8; ++i)
                stsm4(sb + OFF_STG + wg * 8192 + (i >> 2) * 16384 + (pan_addr ^ ((i & 3) << 5)), pack2(xf[8 * i], xf[8 * i + 1]), pack2(xf[8 * i + 2], xf[8 * i + 3]),
                      pack2(xf[8 * i + 4], xf[8 * i + 5]), pack2(xf[8 * i + 6], xf[8 * i + 7]));
            load_table(par, sb + OFF_PAR);
            const LnRow n2 = merge_stats(pub + ((int)q4 * 2 - j) * (S_ / 2), 2, [&] {
                mbar_wait(BAR_EMPTY(sb, (ST_GU - 1) % NSLOT), ((ST_GU - 1) / NSLOT) & 1);
            });
            ln_norm(xr, xf, n2);
            ln_emit(xr, par, sb, wg, ix);
        }
        {
            auto h_at = [&](int col, int per = 8) { IDX(); return pt.hb + (m * 128 + warp * 16 + g8) * F_ + j * 448 + col + q4 * per; };
            uint32_t gu[64];
            {
                float a256[88], a128[88];
                run_own<M_GU3, ST_GU, 0>(a256, a128, pp, wg);
                run<LAG>(24, wg, BAR_ONE(sb, EV_LAG1), [&] { step32<M_GU3>(a256, a128, pp, wg); });
                __nv_bfloat16* const dst = h_at(128, 4);
                pp.drain();
                glu_now<3, 16, 64, 64>(a256, a128, dst);
#pragma unroll
                for (int i = 0; i < 32; ++i) gu[32 + i] = pack2(a128[2 * i], a128[2 * i + 1]);
#pragma unroll
                for (int i = 0; i < 32; ++i) gu[i] = pack2(a256[2 * i], a256[2 * i + 1]);
            }
#pragma unroll 1
            for (int p = 0; p < 2; ++p) {
                float b256[128], none[64];
                pp.at(p ? ST_G1 + 32 : ST_G1);
                fresh(b256);
                step32<M_GU2>(b256, none, pp, wg, 0);
                glu_under(gu, h_at(p * 192), GW + wg, [&] { step32<M_GU2>(b256, none, pp, wg); });
                __syncwarp();
                mbar_arrive_if0(BAR_ONE(sb, EV_HB), lane);
                run<LAGS>(15 - GW - wg, wg, BAR_ONE(sb, EV_LAG2 + p), [&] { step32<M_GU2>(b256, none, pp, wg); });
                pp.drain();
                pack_all(gu, b256);
            }
            float acc[64], xf[64];
            uint4 gt[8];
            pp.at(ST_G1 + 64);
            fresh(acc);
            step64(acc, pp, wg, 0);
            glu_under(gu, h_at(320), GD + wg, [&] { step64(acc, pp, wg); });
            __syncwarp();
            mbar_arrive_if0(BAR_ONE(sb, EV_HB), lane);
            uint32_t x1[32];
#pragma unroll
            for (int i = 0; i < 32; ++i) asm volatile("" : "=r"(x1[i]));
            mbar_wait(BAR_ONE(sb, EV_GB), 0);
            epilogue_operands<2, 0, 8>(xf, gt, x1, sb + OFF_STG + wg * 8192, sb + OFF_TAB + 512, [&](auto f) { step64(acc, pp, wg, 1, -1, f); });
            const uint32_t rows = sb + OFF_STG + wg * 8192 + (warp & 3) * 2048;
            const uint32_t oa = __shfl_sync(0xffffffffu, rows + (lane & 7) * 128 + (((lane >> 3) ^ (lane & 7)) << 4), lane);
            run<LAGD>(23 - GD - wg, wg, BAR_ONE(sb, EV_LAG5), [&] { step64(acc, pp, wg); });
            cluster_arrive();
            mbar_arrive_if0(BAR_SFULL(sb, wg * 2), lane);
            wg_wait<0>();
#pragma unroll
            for (int u = 0; u < 4; ++u) {
                const int p = u >> 1, hf = u & 1;
#pragma unroll
                for (int i = 0; i < 2; ++i) {
                    uint32_t r[4];
#pragma unroll
                    for (int t = 0; t < 4; ++t) {
                        const int e = 32 * p + 16 * i + 4 * t + 2 * hf;
                        r[t] = pack2(fmaf(gate_of(gt, e), acc[e], xf[e]), fmaf(gate_of(gt, e + 1), acc[e + 1], xf[e + 1]));
                    }
                    stsm4((oa ^ (i << 6)) + p * 16384 + hf * 1024, r[0], r[1], r[2], r[3]);
                }
                {
                    if (u < 3) asm volatile("{\n.reg .pred p;\nsetp.eq.u32 p, %0, %1;\nO_LOOP:\nfence.proxy.async.shared::cta;\n@p bra O_LOOP;\n}" :: "r"(blockIdx.y), "r"(2000 + u) : "memory");
                    else fence_async_smem();
                    __syncwarp();
                    if (elect_one()) tma_store(&mp.out, wg * D_ + j * 128 + p * 64, m * 64 + (warp & 3) * 16 + hf * 8, rows + p * 16384 + hf * 1024);
                }
            }
            bulk_commit();
        }
      }
    } else {
        const bool sil = aux || warp == 9 || warp == 10;
        uint4 cv;
        if (sil) cv = *(const uint4*)(cvec + ((aux ? warp : cid) & 3) * 256 + lane * 8);
        uint4* const modp = pt.mail->mod1 + (lane >> 2) * 2048 + (cid & 3) * 512 + ((cid >> 2) * 4 + (warp & 3)) * 4 + (lane & 3);
        if (!aux) st_pkt16(modp, 0, 0, 0, 0);
        uint4 sg = make_uint4(0, 0, 0, 0);
        if (lane < NSEG) sg = pt.sched[(aux * 2 + (warp == 11)) * NSEG + lane];
        if (elect_one()) {
            if (warp == 8) {
                prefetch_map(&mp.ld[aux ? L_WMOD : L_WQKV]);
            } else if (warp < 11) {
#pragma unroll
                for (int i = 0; i < 3; ++i) mbar_init(BAR_FULL(sb, (warp - 9) * 3 + i), 2);
#pragma unroll
                for (int i = 0; i < 2; ++i) mbar_init(BAR_SFULL(sb, (warp - 9) * 2 + i), 4);
#pragma unroll
                for (int i = 0; i < 3; ++i) mbar_init(BAR_EMPTY(sb, (warp - 9) * 3 + i), 4);
            } else {
#pragma unroll
                for (int i = EV_X; i < EV_COUNT; ++i) mbar_init(BAR_ONE(sb, i), i == EV_HB ? 8 : i == EV_ST0 ? 4 : i == EV_P2 ? 2 : 1);
            }
            asm volatile("fence.mbarrier_init.release.cluster;" ::: "memory");
        }
        __syncwarp();
        cluster_arrive();
        cluster_wait();
        const bool el = elect_one();
        const int kown = j * 128;
        auto first_tiles = [&](int i0, int i1) {
#pragma unroll 1
            for (int i = i0; i < i1; ++i) {
                if (el && i < 4) mbar_arrive(BAR_FULL(sb, i));
                if (el) {
                    mbar_expect_tx(BAR_FULL(sb, i), 24576);
                    tma_load5_mc(sb + i * SLOT + 8192 + rank * 12288, &mp.ld[L_WQKV], 0, (i < 4 ? kown + i * 32 : j ? 0 : 128) + rank * 16, 2 * j, 0, 0, BAR_FULL(sb, i));
                }
            }
        };
        if (!aux && warp == 8) {
            mbar_wait(BAR_ONE(sb, EV_WIN), 0);
            if (el) {
                mbar_expect_tx(BAR_ONE(sb, EV_X), 16384);
#pragma unroll
                for (int i = 0; i < 2; ++i) tma_load(sb + OFF_STG + i * 16384, &mp.x, j * 128 + i * 64, m * 64, BAR_ONE(sb, EV_X));
            }
            first_tiles(0, NB0);
        }
        if (sil) {
            const uint32_t s0 = pack2(silu_(bf_lo(cv.x)), silu_(bf_hi(cv.x))), s1 = pack2(silu_(bf_lo(cv.y)), silu_(bf_hi(cv.y))),
                           s2 = pack2(silu_(bf_lo(cv.z)), silu_(bf_hi(cv.z))), s3 = pack2(silu_(bf_lo(cv.w)), silu_(bf_hi(cv.w)));
#pragma unroll
            for (int i = 0; i < 4; ++i) {
                const uint32_t row = aux ? 0 : (warp & 1) * 4 + i;
                sts128(sb + (aux ? OFF_STG + (warp & 3) * 4096 : 4 * SLOT) + (lane >> 3) * 1024 + row * 128 + (((lane & 7) ^ row) << 4), s0, s1, s2, s3);
            }
            fence_async_smem();
        }
        bar_sync(4, 128);
        if (!aux) {
            float acc[32];
#pragma unroll
            for (int i = 0; i < 32; ++i) acc[i] = 0.f;
#pragma unroll 1
            for (int h = 0; h < 4; ++h) {
                mbar_wait(BAR_ONE(sb, EV_WIN + h), 0);
                wg_fence();
#pragma unroll
                for (int k = 0; k < 4; ++k)
                    wgmma_n64<0>(acc, mk_desc(d16(sb) + h * 64, 4 * SLOT + (k >> 2) * 1024 + (k & 3) * 32, 16, 0, 1), mk_desc(d16(sb) + h * 512, OFF_OWN + k * 2048, 8192, 1024, 1));
                wg_commit();
            }
            ep = __shfl_sync(0xffffffffu, ep, 0) / NCTA + 1;
            wg_wait<0>();
            const uint32_t i = warp & 3;
            auto pick = [&](int e) { return __float_as_uint(i & 2 ? (i & 1 ? acc[24 + e] : acc[16 + e]) : (i & 1 ? acc[8 + e] : acc[e])); };
            st_pkt16(modp, (pick(0) & ~3u) | (1 + (ep & 1)), pick(1), pick(4), pick(5));
        } else {
            ep = __shfl_sync(0xffffffffu, ep, 0) / NCTA + 1;
            if (warp == 11) while (!(ld_pkt16(pt.mail->mod1 + 256).x & (1 + (ep & 1)))) __nanosleep(200);
            if (warp == 8) {
                uint32_t v;
                do { __nanosleep(1000); asm volatile("ld.acquire.gpu.global.u32 %0, [%1];" : "=r"(v) : "l"(g_flags + FL_WX) : "memory"); } while (v != 128 * ep);
            }
        }
        asm volatile("setmaxnreg.dec.sync.aligned.u32 %0;" :: "n"(504 - 2 * RC));

        if (warp == 8 || warp == 11) {
            const bool act = warp == 11;
            if (act && !aux) {
                const uint4* pk = pt.mail->mod1 + grp * 2048 + j * 32 + lane;
                uint4 a[8];
                while (true) {
                    uint32_t t = 1 + (ep & 1);
#pragma unroll
                    for (int i = 0; i < 8; ++i) { a[i] = ld_pkt16(pk + i * 256); t &= a[i].x; a[i].x &= ~3u; }
                    if (__all_sync(0xffffffffu, t != 0)) break;
                }
                uint32_t r[4];
#pragma unroll
                for (int v = 0; v < 2; ++v) {
                    auto sum = [&](uint32_t uint4::*f) { return bf_round((__uint_as_float(a[v].*f) + __uint_as_float(a[2 + v].*f)) + (__uint_as_float(a[4 + v].*f) + __uint_as_float(a[6 + v].*f))) + v; };
                    r[2 * v] = pack2(sum(&uint4::x), sum(&uint4::y)); r[2 * v + 1] = pack2(sum(&uint4::z), sum(&uint4::w));
                }
                sts128(sb + OFF_PAR + lane * 16, r[0], r[1], r[2], r[3]);
                __syncwarp();
                if (el) mbar_arrive(BAR_ONE(sb, EV_PAR));
            }
            {
                const uint32_t split = sg.z >> 20, bytes = (sg.z & 63) << 10;
                const uint32_t dst = split ? (split >= 3 ? 16384 : 8192) + rank * (split == 2 ? 4096 : bytes >> 1) : 0;
                const uint32_t blk = ((sg.z >> 8) & 15) * j + ((sg.z >> 12) & 255) + (split == 3 ? rank : 0);
                if (split == 2) sg.x += rank << 24;
                if (split == 1 || split == 4) sg.y |= rank << (12 + (split >> 2));
                sg.z = dst | blk << 16 | (sg.z & 63) << 24;
            }
            if (!act && !aux) {
#pragma unroll 1
                for (int h = 0; h < 2; ++h) { mbar_wait(BAR_ONE(sb, h ? EV_ST0 : EV_PAR), 0); first_tiles(h ? NB1 : NB0, h ? 5 : NB1); }
            }
            Ring r{0, 1};
#pragma unroll 1
            for (int s = 0; ; ++s) {
                const uint32_t x = __shfl_sync(0xffffffffu, sg.x, s), y = __shfl_sync(0xffffffffu, sg.y, s), z = __shfl_sync(0xffffffffu, sg.z, s), w = __shfl_sync(0xffffffffu, sg.w, s);
                const uint32_t nx = __shfl_sync(0xffffffffu, sg.x, s + 1);
                if (!x) break;
                if (el) { prefetch_map(&mp.ld[nx >> 24]); prefetch_map(&mp.ld[(nx >> 24) + 1]); }
                const CUtensorMap* const tm = &mp.ld[x >> 24];
                const uint32_t n = x & 255, blk = (z >> 16) & 255, bytes = (z >> 24) << 10, cnt = w >> 24, base = sb + (z & 0xFFFF);
                if (x & (F_SKIP << 16)) {
                    r.slot += n;
                    if (r.slot >= NSLOT) { r.slot -= NSLOT; r.par ^= 1; }
                    continue;
                }
                uint32_t kl;
                {
                    const uint32_t a = (y >> 2) & 63, step = (y >> 16) & 255, ch = a + lane * (step >> 5), u = ch >> 1, q = u < 7 ? u : u - 7;
                    kl = (y & 3) == K_PANEL ? (q + (q >= j)) * 128 + (u < 7 ? 0 : 64) + (ch & 1) * 32
                                            : ch * 32 + ((lane * ((x >> 8) & 255)) >> 7) * (y >> 24) * 64 + ((y & 3) == K_OWN ? kown : 0);
                    kl += (y >> 8) & 48;
                }
                uint32_t wrap = NSLOT - ((x >> 16) & F_WRAP);
                auto acquire = [&](uint32_t& st, uint32_t& fb) {
                    mbar_wait(BAR_EMPTY(sb, r.slot), r.par);
                    st = base + r.slot * SLOT; fb = BAR_FULL(sb, r.slot);
                    if (++r.slot == wrap) { r.slot = 0; r.par ^= 1; }
                    wrap = NSLOT;
                };
                uint32_t st, fb;
                if (w & 0xFFFF) { mbar_wait(sb + OFF_BAR + (w & 0xFFF8), w & 1); fence_async_global(); }
                const bool twice = el && (x & (F_TWICE << 16));
                if (act) {
                    if (el && (x & (F_JOIN << 16))) mbar_arrive(BAR_ONE(sb, EV_SEC));
                    const bool wm = (x >> 24) == L_WMOD;
                    const uint32_t* const fl = g_flags + ((m + blk) & 15) * 64 + cnt * 16 + ((kl >> 6) & 15);
                    const int row = (x >> 24) == L_X ? m * 64 : (m + blk) * 128;
                    uint32_t ready = cnt ? 0 : ~0u;
                    auto need = [&](uint32_t i, uint32_t bits) {
                        while (!((ready >> i) & 1)) {
                            uint32_t v; asm volatile("ld.relaxed.gpu.global.u32 %0, [%1];" : "=r"(v) : "l"(fl) : "memory");
                            ready = __ballot_sync(0xffffffffu, ((v + 3 - 3 * ep) & bits) == bits);
                            fence_async_global();
                        }
                    };
                    if (x & (F_EARLY << 16)) {
                        const uint32_t k0 = __shfl_sync(0xffffffffu, kl, 0), k2 = __shfl_sync(0xffffffffu, kl, 2);
#pragma unroll
                        for (int e = 0; e < 3; ++e) mbar_wait(BAR_FULL(sb, e), 0);
#pragma unroll 1
                        for (int g = 1; g >= 0; --g) {
                            ready = 0;
#pragma unroll
                            for (int e = 0; e < 4; ++e) {
                                if (!(e & 1)) need(e, 3 - 2 * g);
                                fb = g ? BAR_FULL(sb, e ? e - 1 : 4) : BAR_ONE(sb, EV_A0 + e);
                                if (el) { mbar_expect_tx(fb, 4096); tma_load4(sb + (e ? e - 1 : 4) * SLOT + g * 4096, tm + 1, (e < 2 ? k0 : k2) + (e & 1) * 32, row + g * 64, 0, fb); }
                            }
                        }
                        if (el) mbar_arrive(BAR_ONE(sb, EV_SEC));
                        r.slot = 3; r.par ^= 1;
                    }
#pragma unroll 1
                    for (uint32_t i = (x >> 17) & 4; i < n; ++i) {
                        const uint32_t k = __shfl_sync(0xffffffffu, kl, i);
                        need(i, 3);
                        acquire(st, fb);
                        if (twice) mbar_arrive(fb);
                        if (el) { mbar_expect_tx(fb, bytes); tma_load4(st, tm, wm ? 0 : k, wm ? k : row, wm ? blk : 0, fb); }
                    }
                } else {
                    const bool wd = (x >> 25) == L_WD / 2;
                    const uint32_t more = (x >> 26) == L_WG / 4 ? 1 + (bytes > 16384) : 0;
#pragma unroll 1
                    for (uint32_t i = 0; i < n; ++i) {
                        const uint32_t k = __shfl_sync(0xffffffffu, kl, i);
                        acquire(st, fb);
                        if (twice) mbar_arrive(fb);
                        if (el) { mbar_expect_tx(fb, bytes); tma_load5_mc(st, tm, wd ? blk * 64 : 0, wd ? 0 : k, wd ? 0 : blk, (x >> 24) == L_WKV, wd ? k >> (5 - ((x >> 24) & 1)) : 0, fb); }
                        if (more && el) tma_load5_mc(st + 4096 + more * 4096, tm, 0, k, blk + 1, 0, 0, fb);
                        if (more > 1 && el) tma_load5_mc(st + 8192 + rank * 8192, tm, 0, k, blk + 2, 0, 0, fb);
                    }
                }
            }
        } else if (aux) {
            if (warp == 10) {
#pragma unroll 1
                for (int p = 0; p < 4; ++p) {
                    mbar_wait_b(BAR_ONE(sb, EV_HB), p & 1);
                    if (el) asm volatile("red.release.gpu.global.add.u32 [%0], 1;" :: "l"(g_flags + (m + 2 * p) * 64 + 3) : "memory");
                }
            }
        } else {
            const uint32_t w = warp - 9;
            uint32_t bpar = 0;
            auto send = [&](int t) {
                const CUtensorMap* const tm = t ? &mp.os : &mp.h1s;
                const bool ring = t != 1;
                const uint32_t src = sb + (ring ? OFF_OWN : OFF_STG), par = t & 1;
#pragma unroll 1
                for (uint32_t u = w ? 0 : 1; u < (w ? 1 : 3); ++u) {
                    const uint32_t p = u >> 1, g1 = !(ring && u == 1), g0 = u == 0;
                    if (p && ring) mbar_wait_b(BAR_ONE(sb, EV_SEC), t >> 1);
                    const int col = kown + p * 64, row = m * 128 + g0 * 64;
                    const uint32_t back = BAR_ONE(sb, EV_BACK + w), from = src + p * 16384;
                    if (g1 != g0) {
                        mbar_wait_b(BAR_SFULL(sb, 2 + p), par);
                        if (el) { fence_async_smem(); tma_store(tm, col, row + 64, from + 8192); }
                    }
                    mbar_wait_b(BAR_SFULL(sb, 2 * g0 + p), par);
                    if (el) {
                        fence_async_smem();
                        tma_store(tm, col, row, from + g0 * 8192);
                        bulk_commit();
                        mbar_expect_tx(back, 2048);
                        bulk_wait_all();
#pragma unroll
                        for (int i = 0; i < 4; ++i) tma_load(sb + OFF_JUNK, tm + 2, col, row + (i & 1) * 32 + (i >> 1) * (g1 - g0) * 64, back);
                    }
                    __syncwarp();
                    if (p && ring) {
                        mbar_wait_b(BAR_FULL(sb, 5), 0); mbar_wait_b(BAR_ONE(sb, EV_BACK + 1), t >> 1);
                        if (lane < 4) asm volatile("{\n.reg .b32 r;\nmapa.shared::cluster.u32 r, %0, %1;\nmbarrier.arrive.shared::cluster.b64 _, [r];\n}" :: "r"(BAR_EMPTY(sb, 5)), "r"(lane & 1) : "memory");
                    }
                    mbar_wait_b(back, bpar);
                    bpar ^= 1;
                    if (el) asm volatile("red.relaxed.gpu.global.add.u32 [%0], %1;" :: "l"(g_flags + m * 64 + 16 + t * 16 + 2 * j + p), "r"(g1 + 2 - 2 * g0) : "memory");
                }
            };
            auto gate = [&](int vec, int ev) {
                uint2 a, b; uint32_t n = 0;
                const uint2* src = g_mod + vec * 512 + j * 64 + (lane >> 2) * 8 + (lane & 3);
                while (true) {
                    a = ld_pkt(src); b = ld_pkt(src + 4);
                    if (__all_sync(0xffffffffu, a.y == ep && b.y == ep)) break;
                    SPIN_GUARD(n); __nanosleep(300);
                }
                sts128(sb + OFF_TAB + (ev - EV_GA) * 512 + lane * 16, a.x << 16, a.x & 0xFFFF0000u, b.x << 16, b.x & 0xFFFF0000u);
                __syncwarp();
                if (el) mbar_arrive(BAR_ONE(sb, ev));
            };
            if (lane < 6) prefetch_map(lane < 4 ? &mp.h1s + lane : &mp.ld[L_H1 - 4 + lane]);
            auto count = [&](int f, uint32_t n_in = 8) {
                uint32_t v, n = 0;
                while (true) {
                    asm volatile("ld.acquire.gpu.global.u32 %0, [%1];" : "=r"(v) : "l"(g_flags + f) : "memory");
                    if ((int32_t)(v - ep * n_in) >= 0) break;
                    SPIN_GUARD(n); __nanosleep(300);
                }
            };
#pragma unroll 1
            for (int t = 0; t < 3; t += 1 + w) {
                send(t);
                if (w == 0) {
                    if (t && el) mbar_arrive(BAR_ONE(sb, t == 1 ? EV_P2 : EV_SENT));
                    if (t == 1 && m > 0) {
#pragma unroll 4
                        for (int i = 0; i < 16; ++i) (g_halo + ((m - 1) * 8 + j) * 512 + lane)[i * 32] = make_uint4(0, 0, 0, 0);
                    }
                } else {
                    gate(t ? 5 : 2, t ? EV_GB : EV_GA);
                    if (t == 0) {
                        const uint4* src = (const uint4*)((rank ? pt.wu : pt.wg) + ((cid >> 1) * 16 + (lane >> 4)) * F_ + ((lane >> 1) & 7) * 448 + 176) + (lane & 1);
                        uint4* dst = (uint4*)(pt.wx + (rank * D_ + (cid >> 1) * 16) * 128) + lane;
#pragma unroll 2
                        for (int i = 0; i < 8; ++i) dst[i * 32] = __ldcg(src + i * (F_ / 4));
                        __syncwarp();
                        __nanosleep(RESTH);
                        if (el) asm volatile("red.release.gpu.global.add.u32 [%0], 1;" :: "l"(g_flags + FL_WX) : "memory");
                        count(FL_LN2);
                        const uint4 v = __ldcg((const uint4*)(g_par2 + j * 128) + lane);
                        mbar_wait_b(BAR_SFULL(sb, 2), 1);
                        sts128(sb + OFF_PAR + lane * 16, v.x, v.y, v.z, v.w);
                        __syncwarp();
                        if (el) mbar_arrive(BAR_ONE(sb, EV_P2));
                    }
                }
            }
            if (!w && el) flag_add(g_flags + FL_DONE);
            if (w) {
#pragma unroll 1
                for (int p = 0; p < 4; ++p) {
                    if (p < 3) {
                        mbar_wait_b(BAR_ONE(sb, EV_HB), p & 1);
                        __nanosleep(RESTH);
                        if (el) asm volatile("red.release.gpu.global.add.u32 [%0], 1;" :: "l"(g_flags + m * 64 + p) : "memory");
                    }
                    count(m * 64 + p, p < 3 ? 8 : 1);
                    if (el) mbar_arrive(BAR_ONE(sb, EV_H + p));
                }
            }
            cluster_arrive_early = true;
            cluster_arrive();
            mbar_wait_b(BAR_SFULL(sb, w * 2), 1);
        }
        __syncwarp();
    }
    if (aux || (wg == 2 && !cluster_arrive_early)) cluster_arrive();
    cluster_wait();
    bulk_wait_read();
    if (tid == 0) {
        if (aux) flag_add(pt.mail->flags + FL_DONE);
    }
}

typedef CUresult (*EncodeFn)(CUtensorMap*, CUtensorMapDataType, cuuint32_t, void*, const cuuint64_t*, const cuuint64_t*, const cuuint32_t*,
                             const cuuint32_t*, CUtensorMapInterleave, CUtensorMapSwizzle, CUtensorMapL2promotion, CUtensorMapFloatOOBfill);

void make_map(EncodeFn fn, CUtensorMap* m, const void* ptr, uint64_t rows, uint64_t cols, uint32_t brows, uint32_t bcols) {
    cuuint64_t dims[2] = {cols, rows}, strides[1] = {cols * 2};
    cuuint32_t box[2] = {bcols, brows}, es[2] = {1, 1};
    fn(m, CU_TENSOR_MAP_DATA_TYPE_BFLOAT16, 2, (void*)ptr, dims, strides, box, es, CU_TENSOR_MAP_INTERLEAVE_NONE,
       bcols == 64 ? CU_TENSOR_MAP_SWIZZLE_128B : bcols == 32 ? CU_TENSOR_MAP_SWIZZLE_64B : CU_TENSOR_MAP_SWIZZLE_NONE,
       bcols == 8 ? CU_TENSOR_MAP_L2_PROMOTION_NONE : CU_TENSOR_MAP_L2_PROMOTION_L2_128B, CU_TENSOR_MAP_FLOAT_OOB_FILL_NONE);
}
struct View { uint64_t dim[5], stride[4]; uint32_t box[5]; };
void make_view(EncodeFn fn, CUtensorMap* m, const void* ptr, uint32_t rank, const View& v) {
    cuuint64_t dims[5], strides[4];
    cuuint32_t box[5], es[5] = {1, 1, 1, 1, 1};
    for (int i = 0; i < 5; ++i) { dims[i] = v.dim[i]; box[i] = v.box[i]; if (i < 4) strides[i] = v.stride[i] * 2; }
    fn(m, CU_TENSOR_MAP_DATA_TYPE_BFLOAT16, rank, (void*)ptr, dims, strides, box, es, CU_TENSOR_MAP_INTERLEAVE_NONE,
       box[0] == 64 ? CU_TENSOR_MAP_SWIZZLE_128B : CU_TENSOR_MAP_SWIZZLE_64B, CU_TENSOR_MAP_L2_PROMOTION_L2_128B, CU_TENSOR_MAP_FLOAT_OOB_FILL_NONE);
}

}

extern "C" void kernel_launch(void* const* d_in, const int* in_sizes, int n_in, void* d_out, int out_size) {
    (void)in_sizes; (void)n_in; (void)out_size;
    void* fnp = nullptr;
    cudaDriverEntryPointQueryResult qr;
    cudaGetDriverEntryPoint("cuTensorMapEncodeTiled", &fnp, cudaEnableDefault, &qr);
    EncodeFn fn = (EncodeFn)fnp;
    void *h1, *o, *hb, *mail, *sched, *wx;
    cudaGetSymbolAddress(&h1, g_h1);
    cudaGetSymbolAddress(&mail, g_mail);
    cudaGetSymbolAddress(&o, g_o);
    cudaGetSymbolAddress(&hb, g_hb);
    cudaGetSymbolAddress(&sched, g_sched);
    cudaGetSymbolAddress(&wx, g_wx);
    Maps mp;
    auto wmap = [&](int i, const void* p, uint64_t rows, uint64_t cols, uint64_t sec, uint32_t brows, uint32_t bblk, uint32_t bsec) {
        make_view(fn, &mp.ld[i], p, i == L_WMOD ? 4 : 5, View{{64, rows, cols / sec / 64, sec, 1}, {cols, 64, cols / sec, 64}, {64, brows, bblk, bsec, 1}});
    };
    auto amap = [&](int i, const void* p, uint64_t cols, uint32_t bcols, uint32_t brows = 128) { make_view(fn, &mp.ld[i], p, 4, View{{cols, S_, 1, 1, 1}, {cols, 64, 64, 64}, {bcols, brows, 1, 1, 1}}); };
    wmap(L_WQKV, d_in[1], D_, 3 * D_, 3, 16, 2, 3);
    wmap(L_WKV, d_in[1], D_, 3 * D_, 3, 16, 2, 2);
    wmap(L_WQ, d_in[1], D_, 3 * D_, 3, 64, 1, 1);
    wmap(L_WQ1, d_in[1], D_, 3 * D_, 3, 32, 1, 1);
    wmap(L_WO, d_in[2], D_, D_, 1, 64, 1, 1);
    wmap(L_WG, d_in[4], D_, F_, 1, 32, 1, 1);
    wmap(L_WU, d_in[5], D_, F_, 1, 32, 1, 1);
    for (int i = 0; i < 2; ++i) wmap(L_WGX + i, (const __nv_bfloat16*)wx + i * D_ * 128, D_, 128, 1, 32, 1, 1);
    make_view(fn, &mp.ld[L_WD3], d_in[6], 5, View{{D_, 2, 2, 4, F_ / 16}, {D_, 8 * D_, 2 * D_, 16 * D_}, {64, 2, 2, 4, 4}});
    make_view(fn, &mp.ld[L_WD], d_in[6], 5, View{{D_, 2, 4, 4, F_ / 32}, {D_, 8 * D_, 2 * D_, 32 * D_}, {64, 2, 4, 4, 2}});
    wmap(L_WMOD, d_in[8], D_, 6 * D_, 1, 64, 4, 1);
    amap(L_H1, h1, D_, 32); amap(L_H1Q, h1, D_, 64); amap(L_O, o, D_, 64); amap(L_H2, o, D_, 32); amap(L_HB, hb, F_, 64);
    amap(L_H1E, h1, D_, 32, 64); amap(L_H2E, o, D_, 32, 64);
    make_view(fn, &mp.ld[L_X], d_in[0], 4, View{{D_, S_ / 2, 2, 1, 1}, {2 * D_, D_, 64, 64}, {64, 64, 2, 1, 1}});
    make_map(fn, &mp.h1s, h1, S_, D_, 64, 64);
    make_map(fn, &mp.os, o, S_, D_, 64, 64);
    make_map(fn, &mp.h1r, h1, S_, D_, 32, 8);
    make_map(fn, &mp.orr, o, S_, D_, 32, 8);
    make_map(fn, &mp.wm, d_in[8], D_, 6 * D_, 64, 64);
    make_map(fn, &mp.x, d_in[0], S_ / 2, 2 * D_, 64, 64);
    make_map(fn, &mp.out, d_out, S_ / 2, 2 * D_, 8, 64);
    cudaFuncSetAttribute(fused_block_kernel, cudaFuncAttributeMaxDynamicSharedMemorySize, SMEM_BYTES);
    cudaLaunchConfig_t cfg = {};
    cfg.gridDim = dim3(NCTA); cfg.blockDim = dim3(384); cfg.dynamicSmemBytes = SMEM_BYTES; cfg.stream = cudaStreamPerThread;
    cudaLaunchAttribute at[1];
    at[0].id = cudaLaunchAttributeClusterDimension; at[0].val.clusterDim.x = 2; at[0].val.clusterDim.y = 1; at[0].val.clusterDim.z = 1;
    cfg.attrs = at; cfg.numAttrs = 1;
    const Ptrs pt{(const __nv_bfloat16*)d_in[7], (Mail*)mail, (__nv_bfloat16*)hb, (const uint4*)sched, (const __nv_bfloat16*)d_in[0], (const __nv_bfloat16*)d_in[4], (const __nv_bfloat16*)d_in[5], (__nv_bfloat16*)wx};
    cudaLaunchKernelEx(&cfg, fused_block_kernel, pt, mp);
}
```
